```python
import torch

def _softmax(x, axis=-1):
    return torch.softmax(x, dim=axis)

def _gelu(x):
    return torch.nn.functional.gelu(x, approximate='tanh')

def _silu(x):
    return torch.nn.functional.silu(x)

def _sigmoid(x):
    return torch.sigmoid(x)

def _layernorm(x, axis=-1, eps=1e-05):
    m = x.mean(dim=axis, keepdim=True)
    v = x.var(dim=axis, keepdim=True, unbiased=False)
    return (x - m) / torch.sqrt(v + eps)

def _scatter_add(tgt, idx, src, axis=0):
    return tgt.clone().index_add_(axis, idx, src)

def _segment_sum(src, seg, n):
    out = torch.zeros((n,) + src.shape[1:], dtype=src.dtype)
    return out.index_add_(0, seg, src)

def _pad(x, pw):
    flat = tuple((v for pair in reversed(pw) for v in pair))
    return torch.nn.functional.pad(x, flat)
kernel_name = 'adaLN_cond__gqa_block_cached__glu_gated_swiglu__decode'

def setup_inputs():

    _w = lambda a: (lambda t: t.to(torch.bfloat16) if t.is_floating_point() else t)(torch.as_tensor(a))

    def _A_setup():
        B, Sq, D = (2, 1, 576)
        Hq, Hkv, Sk, Dh = (32, 16, 8192, 128)
        assert Hq % Hkv == 0, (Hq, Hkv)
        return {'x': _w((lambda *s: torch.randn(*s, dtype=torch.bfloat16) * 0.1)(B, Sq, D)), 'k_cache': _w((lambda *s: torch.randn(*s, dtype=torch.bfloat16) * 0.8)(B, Hkv, Sk, Dh)), 'v_cache': _w((lambda *s: torch.randn(*s, dtype=torch.bfloat16) * 3.2)(B, Hkv, Sk, Dh)), 'wq': _w((lambda *s: torch.randn(*s, dtype=torch.bfloat16) * 0.8)(D, Hq * Dh) * D ** (-0.5)), 'wo': _w((lambda *s: torch.randn(*s, dtype=torch.bfloat16) * 3.2)(Hq * Dh, D) * (Hq * Dh) ** (-0.5))}
    _A_in = _A_setup()

    def _B_setup():
        B, S, D, F = (2, 1, 576, 4608)
        return {'x': _w((lambda *s: torch.randn(*s, dtype=torch.bfloat16) * 0.1)(B, S, D)), 'w1': _w((lambda *s: torch.randn(*s, dtype=torch.bfloat16) * 3.2)(D, F) * (2.0 / D) ** 0.5), 'w3': _w((lambda *s: torch.randn(*s, dtype=torch.bfloat16) * 3.2)(D, F) * (2.0 / D) ** 0.5), 'w2': _w((lambda *s: torch.randn(*s, dtype=torch.bfloat16) * 3.2)(F, D) * (2.0 / F) ** 0.5)}
    _B_in = _B_setup()
    return {'A_x': _A_in['x'], 'A_k_cache': _A_in['k_cache'], 'A_v_cache': _A_in['v_cache'], 'A_wq': _A_in['wq'], 'A_wo': _A_in['wo'], 'B_x': _B_in['x'], 'B_w1': _B_in['w1'], 'B_w3': _B_in['w3'], 'B_w2': _B_in['w2'], 'c': _w((lambda *s: torch.randn(*s, dtype=torch.bfloat16) * 0.4)(2, 576) * 8.0), 'w_mod': _w((lambda *s: torch.randn(*s, dtype=torch.bfloat16) * 0.4)(576, 6 * 576) * 576 ** (-0.5) * 8.0)}

def reference(A_x, A_k_cache, A_v_cache, A_wq, A_wo, B_x, B_w1, B_w3, B_w2, c, w_mod):

    def _A_ref(x, k_cache, v_cache, wq, wo):
        B, Sq, D = x.shape
        Hq, Dh = (32, 128)
        Hkv = k_cache.shape[1]
        rep = Hq // Hkv
        q = (lambda x, *d: x.permute(*d))((x @ wq).reshape(B, Sq, Hq, Dh), 0, 2, 1, 3)
        k = (lambda x, n, axis: torch.repeat_interleave(x, n, dim=axis))(k_cache, rep, axis=1)
        v = (lambda x, n, axis: torch.repeat_interleave(x, n, dim=axis))(v_cache, rep, axis=1)
        scores = torch.einsum('bhqd,bhkd->bhqk', q, k) * Dh ** (-0.5)
        p = _softmax(scores, axis=-1)
        o = torch.einsum('bhqk,bhkd->bhqd', p, v)
        return (lambda x, *d: x.permute(*d))(o, 0, 2, 1, 3).reshape(B, Sq, Hq * Dh) @ wo

    def _B_ref(x, w1, w3, w2):
        gate = torch.einsum('bsd,df->bsf', x, w1)
        up = torch.einsum('bsd,df->bsf', x, w3)
        h = _silu(gate) * up
        out = torch.einsum('bsf,fd->bsd', h, w2)
        return out
    x = A_x
    mod = (_silu(c) @ w_mod).reshape(c.shape[0], 6, 1, -1)
    sa, ca, ga, sb, cb, gb = (mod[:, 0].clone(), mod[:, 1].clone(), mod[:, 2].clone(), mod[:, 3].clone(), mod[:, 4].clone(), mod[:, 5].clone())
    h = _layernorm(x, axis=-1) * (1 + ca) + sa
    x = x + ga * _A_ref(h, A_k_cache, A_v_cache, A_wq, A_wo)
    h = _layernorm(x, axis=-1) * (1 + cb) + sb
    x = x + gb * _B_ref(h, B_w1, B_w3, B_w2)
    return x
```

```cpp
#include <cuda_runtime.h>
#include <cuda.h>
#include <cuda_bf16.h>
#include <stdint.h>

namespace {

constexpr int D_   = 576;
constexpr int HKV  = 16;
constexpr int SK   = 8192;
constexpr int DH   = 128;
constexpr int FF   = 4608;
constexpr int NQ   = 4096;
constexpr int NMOD = 6 * D_;

constexpr int NCTA     = 128;
constexpr int NCW      = 9;
constexpr int NCT      = NCW * 32;
constexpr int NTHREADS = NCT + 32;
constexpr int KEYS_PER_CTA = SK / 4;
constexpr int TILE_KEYS = 64;
constexpr int NTILES   = KEYS_PER_CTA / TILE_KEYS;
constexpr int NITEMS   = 2 * NTILES;
constexpr int TILE_BYTES = TILE_KEYS * DH * 2;
constexpr int NRING = 8;
constexpr int BOX_BYTES = 64 * 64;
constexpr int PLANE_BYTES = 9 * BOX_BYTES;
constexpr int ROWB = D_ * 2;

#define TUNE_DH 2
#define TUNE_DB 4
#define TUNE_DT 2
#define TUNE_JTAIL 61
#define TUNE_PACE 1
#define TUNE_PACE_TH 128
#define TUNE_PACE_UP 2
#define TUNE_PACE_DN 2
#define TUNE_PACE_BIAS 288
#define TUNE_JM2 3
#define TUNE_PRE 26
#define TUNE_JMID 40

constexpr int NM1CTA = 36;
constexpr int NMODCTA = NMOD / 32;
constexpr int NWO_CTA = 96;
constexpr int NRED_CTA = 72;

constexpr int SM_RING  = 0;
constexpr int SM_X     = NRING * TILE_BYTES;
constexpr int SM_XA    = SM_X;
constexpr int SM_XB    = SM_X + PLANE_BYTES;
constexpr int SM_XW2E  = SM_X + PLANE_BYTES;
constexpr int SM_W1B8  = 186880;
constexpr int SM_W3B8  = SM_W1B8 + BOX_BYTES;
constexpr int SM_W2G7  = SM_W3B8 + BOX_BYTES + 112;
constexpr int SM_MISC  = SM_X + 2 * PLANE_BYTES;
constexpr int SM_BAR   = SM_MISC;
constexpr int SM_SP    = SM_BAR + 256;
constexpr int HSTRIDE  = 584;
constexpr int SM_SC    = SM_SP + 8192;
constexpr int SM_HB    = SM_SC + 2 * HSTRIDE * 2;
constexpr int SM_RED   = SM_HB + 2 * HSTRIDE * 2;
constexpr int SM_MB    = SM_RED + 9 * 192 * 4;
constexpr int QSTRIDE  = 136;
constexpr int SM_QS    = SM_MB + D_ * 8;
constexpr int VPSTRIDE = 56;
constexpr int SM_VP    = SM_QS + 2 * QSTRIDE * 2;
constexpr int SM_ST    = SM_VP + 2 * VPSTRIDE * 2;
constexpr int SM_FAC   = SM_ST + 9 * 16;
constexpr int SM_HIST  = SM_FAC + 16;
constexpr int SM_TOTAL = SM_HIST + 64;
static_assert(SM_TOTAL <= 232448, "smem");
static_assert(SM_W2G7 + 4 * ROWB <= SM_MISC, "smem");
static_assert(SM_X + 8 * (6 * ROWB + 16) <= SM_W1B8, "smem");
static_assert((SM_ST % 16) == 0 && (SM_RED % 16) == 0 && (SM_MB % 16) == 0 && (SM_SP % 16) == 0, "align");

enum { B_KVFULL = 0, B_KVEMPTY = 8, B_WM = 16, B_WQ = 18, B_W1 = 20, B_W3 = 22, B_W2 = 24, B_MID = 26, B_XFREE = 27, B_FAC = 28 };
constexpr int SM_W1 = SM_RING, SM_W3 = SM_RING + 32768, SM_W2 = SM_RING + 65536;

typedef unsigned long long u64;
struct __align__(128) Scratch {
    u64 h1[4][D_];
    u64 mod[2][D_][2];
    u64 q[2][NQ / 2];
    u64 ml[NCTA][16];
    u64 o[NCTA][2][8][8][2];
    u64 p2[NWO_CTA][D_][2];
    u64 x1[4][NRED_CTA][16];
    u64 p4[NCTA][D_][2];
    unsigned int epoch;
    unsigned int pad_[31];
    unsigned int prog;
};
__device__ Scratch g_s;

#define TS(i)
#define TSL(i)

__device__ __forceinline__ uint32_t smem_u32(const void* p) { return (uint32_t)__cvta_generic_to_shared(p); }
__device__ __forceinline__ float bfr(float x) { return __bfloat162float(__float2bfloat16_rn(x)); }
__device__ __forceinline__ uint32_t pack_bf(float lo, float hi) {
    uint32_t r; asm("cvt.rn.bf16x2.f32 %0, %1, %2;" : "=r"(r) : "f"(hi), "f"(lo)); return r;
}
__device__ __forceinline__ float bf_lo(uint32_t v) { return __uint_as_float(v << 16); }
__device__ __forceinline__ float bf_hi(uint32_t v) { return __uint_as_float(v & 0xffff0000u); }
__device__ __forceinline__ uint32_t hsub2(uint32_t a, uint32_t b) { uint32_t r; asm("sub.rn.bf16x2 %0, %1, %2;" : "=r"(r) : "r"(a), "r"(b)); return r; }
__device__ __forceinline__ uint32_t hadd2(uint32_t a, uint32_t b) { uint32_t r; asm("add.rn.bf16x2 %0, %1, %2;" : "=r"(r) : "r"(a), "r"(b)); return r; }
__device__ __forceinline__ uint32_t hmul2(uint32_t a, uint32_t b) { uint32_t r; asm("mul.rn.bf16x2 %0, %1, %2;" : "=r"(r) : "r"(a), "r"(b)); return r; }
__device__ __forceinline__ float ex2(float x) { float r; asm("ex2.approx.ftz.f32 %0, %1;" : "=f"(r) : "f"(x)); return r; }
__device__ __forceinline__ float rcp(float x) { float r; asm("rcp.approx.ftz.f32 %0, %1;" : "=f"(r) : "f"(x)); return r; }
constexpr float LOG2E = 1.4426950408889634f;
__device__ __forceinline__ float silu_f(float x) { return x * rcp(1.0f + ex2(-x * LOG2E)); }

__device__ __forceinline__ void mbar_init(uint32_t bar, int cnt) { asm volatile("mbarrier.init.shared::cta.b64 [%0], %1;" ::"r"(bar), "r"(cnt)); }
__device__ __forceinline__ void mbar_expect_tx(uint32_t bar, uint32_t bytes) { asm volatile("mbarrier.arrive.expect_tx.shared::cta.b64 _, [%0], %1;" ::"r"(bar), "r"(bytes) : "memory"); }
__device__ __forceinline__ void mbar_arrive(uint32_t bar) { asm volatile("mbarrier.arrive.shared::cta.b64 _, [%0];" ::"r"(bar) : "memory"); }
__device__ __forceinline__ bool mbar_try(uint32_t bar, uint32_t parity) {
    uint32_t ok;
    asm volatile("{\n.reg .pred p;\nmbarrier.try_wait.parity.shared::cta.b64 p, [%1], %2;\nselp.u32 %0, 1, 0, p;\n}\n" : "=r"(ok) : "r"(bar), "r"(parity) : "memory");
    return ok != 0;
}
__device__ __forceinline__ bool mbar_test(uint32_t bar, uint32_t parity) {
    uint32_t ok;
    asm volatile("{\n.reg .pred p;\nmbarrier.test_wait.parity.shared::cta.b64 p, [%1], %2;\nselp.u32 %0, 1, 0, p;\n}\n" : "=r"(ok) : "r"(bar), "r"(parity) : "memory");
    return ok != 0;
}
__device__ __forceinline__ void mbar_wait(uint32_t bar, uint32_t parity) {
    uint32_t spins = 0;
    while (!mbar_try(bar, parity)) { if (++spins > (1u << 22)) __trap(); }
}
__device__ __forceinline__ void bulk_g2s(uint32_t dst, const void* src, uint32_t bytes, uint32_t bar, uint64_t pol) {
    asm volatile("cp.async.bulk.shared::cluster.global.mbarrier::complete_tx::bytes.L2::cache_hint [%0], [%1], %2, [%3], %4;" ::"r"(dst), "l"(src), "r"(bytes), "r"(bar), "l"(pol) : "memory");
}
__device__ __forceinline__ void tma2d(uint32_t dst, const CUtensorMap* map, int c0, int c1, uint32_t bar, uint64_t pol) {
    asm volatile("cp.async.bulk.tensor.2d.shared::cluster.global.mbarrier::complete_tx::bytes.L2::cache_hint [%0], [%1, {%2, %3}], [%4], %5;"
                 ::"r"(dst), "l"(map), "r"(c0), "r"(c1), "r"(bar), "l"(pol) : "memory");
}
__device__ __forceinline__ void cp16(uint32_t dst, const void* src) { asm volatile("cp.async.cg.shared.global [%0], [%1], 16;" ::"r"(dst), "l"(src) : "memory"); }
__device__ __forceinline__ void cp_mbar_arrive(uint32_t bar) { asm volatile("cp.async.mbarrier.arrive.noinc.shared::cta.b64 [%0];" ::"r"(bar) : "memory"); }
__device__ __forceinline__ void csync() { asm volatile("bar.sync 1, 288;" ::: "memory"); }
__device__ __forceinline__ void async8() { asm volatile("bar.sync 2, 256;" ::: "memory"); }

__device__ __forceinline__ void ldsm4(uint32_t (&r)[4], uint32_t addr) {
    asm volatile("ldmatrix.sync.aligned.m8n8.x4.shared.b16 {%0,%1,%2,%3}, [%4];" : "=r"(r[0]), "=r"(r[1]), "=r"(r[2]), "=r"(r[3]) : "r"(addr) : "memory");
}
__device__ __forceinline__ void ldsm4t(uint32_t (&r)[4], uint32_t addr) {
    asm volatile("ldmatrix.sync.aligned.m8n8.x4.trans.shared.b16 {%0,%1,%2,%3}, [%4];" : "=r"(r[0]), "=r"(r[1]), "=r"(r[2]), "=r"(r[3]) : "r"(addr) : "memory");
}
__device__ __forceinline__ void mma16816(float (&d)[4], uint32_t a0, uint32_t a1, uint32_t a2, uint32_t a3, uint32_t b0, uint32_t b1) {
    asm("mma.sync.aligned.m16n8k16.row.col.f32.bf16.bf16.f32 {%0,%1,%2,%3}, {%4,%5,%6,%7}, {%8,%9}, {%0,%1,%2,%3};"
                 : "+f"(d[0]), "+f"(d[1]), "+f"(d[2]), "+f"(d[3]) : "r"(a0), "r"(a1), "r"(a2), "r"(a3), "r"(b0), "r"(b1));
}
__device__ __forceinline__ uint32_t lds32(uint32_t addr) { uint32_t v; asm volatile("ld.shared.u32 %0, [%1];" : "=r"(v) : "r"(addr) : "memory"); return v; }
__device__ __forceinline__ float ldsf(uint32_t addr) { float v; asm volatile("ld.shared.f32 %0, [%1];" : "=f"(v) : "r"(addr) : "memory"); return v; }
__device__ __forceinline__ uint4 lds128(uint32_t addr) { uint4 v; asm volatile("ld.shared.v4.u32 {%0,%1,%2,%3}, [%4];" : "=r"(v.x), "=r"(v.y), "=r"(v.z), "=r"(v.w) : "r"(addr) : "memory"); return v; }
__device__ __forceinline__ void sts32(uint32_t addr, uint32_t v) { asm volatile("st.shared.u32 [%0], %1;" ::"r"(addr), "r"(v) : "memory"); }
__device__ __forceinline__ void sts16(uint32_t addr, float v) { asm volatile("{\n.reg .b16 h;\ncvt.rn.bf16.f32 h, %1;\nst.shared.b16 [%0], h;\n}\n" ::"r"(addr), "f"(v) : "memory"); }
__device__ __forceinline__ void sts64(uint32_t addr, uint32_t a, uint32_t b) { asm volatile("st.shared.v2.u32 [%0], {%1,%2};" ::"r"(addr), "r"(a), "r"(b) : "memory"); }
__device__ __forceinline__ void sts64f(uint32_t addr, float a, float b) { asm volatile("st.shared.v2.f32 [%0], {%1,%2};" ::"r"(addr), "f"(a), "f"(b) : "memory"); }
__device__ __forceinline__ void sts128(uint32_t addr, uint4 v) { asm volatile("st.shared.v4.u32 [%0], {%1,%2,%3,%4};" ::"r"(addr), "r"(v.x), "r"(v.y), "r"(v.z), "r"(v.w) : "memory"); }

__device__ __forceinline__ void st_pkt(u64* p, uint32_t v, uint32_t tag) {
    asm volatile("{\n.reg .b64 t;\nmov.b64 t, {%1,%2};\nst.relaxed.gpu.global.b64 [%0], t;\n}\n" ::"l"(p), "r"(v), "r"(tag) : "memory");
}
__device__ __forceinline__ void st_pkt2(u64* p, uint32_t a, uint32_t b, uint32_t tag) {
    asm volatile("{\n.reg .b64 t,u;\nmov.b64 t, {%1,%3};\nmov.b64 u, {%2,%3};\nst.relaxed.gpu.global.v2.b64 [%0], {t,u};\n}\n" ::"l"(p), "r"(a), "r"(b), "r"(tag) : "memory");
}
template <int OFF>
__device__ __forceinline__ void st_pkt2_if(bool p, const u64* base, float a, float b, uint32_t tag) {
    asm volatile("{\n.reg .pred p;\n.reg .b64 t,u;\nsetp.ne.u32 p, %4, 0;\nmov.b64 t, {%1,%3};\nmov.b64 u, {%2,%3};\n@p st.relaxed.gpu.global.v2.b64 [%0+%5], {t,u};\n}\n"
                 ::"l"(base), "r"(__float_as_uint(a)), "r"(__float_as_uint(b)), "r"(tag), "r"((uint32_t)p), "n"(OFF) : "memory");
}
__device__ __forceinline__ uint4 ld_pkt2(const u64* p) {
    uint4 v;
    asm volatile("{\n.reg .b64 t,u;\nld.relaxed.gpu.global.v2.b64 {t,u}, [%4];\nmov.b64 {%0,%1}, t;\nmov.b64 {%2,%3}, u;\n}\n"
                 : "=r"(v.x), "=r"(v.y), "=r"(v.z), "=r"(v.w) : "l"(p) : "memory");
    return v;
}
template <int N>
__device__ __forceinline__ void pollN(const u64* p, int stride, uint32_t tag, uint32_t (&a)[N], uint32_t (&b)[N]) {
    uint32_t spins = 0;
    while (true) {
        uint4 v[N];
#pragma unroll
        for (int i = 0; i < N; i++) v[i] = ld_pkt2(p + (size_t)i * stride);
        uint32_t bad = 0;
#pragma unroll
        for (int i = 0; i < N; i++) { bad |= (v[i].y ^ tag) | (v[i].w ^ tag); a[i] = v[i].x; b[i] = v[i].z; }
        if (!__any_sync(0xffffffffu, bad != 0)) break;
        if (++spins > (1u << 22)) __trap();
    }
}

__device__ __noinline__ void plane_gemv(uint32_t plane, uint32_t vec, uint32_t red, int warp, int lane) {
    const int g = lane >> 2, c = lane & 3, mi = lane >> 3, kap = lane & 7;
    const int rowl = kap + 8 * (mi >> 1);
    const uint32_t a0 = plane + warp * BOX_BYTES + rowl * 64 + ((((mi & 1)) ^ ((rowl >> 1) & 3)) << 4);
    const uint32_t bo = vec + (g & 1) * (HSTRIDE * 2) + warp * 128 + c * 4;
    float acc0[4] = {0.f, 0.f, 0.f, 0.f}, acc1[4] = {0.f, 0.f, 0.f, 0.f};
#pragma unroll
    for (int s = 0; s < 4; s++) {
        uint32_t x[4], y[4];
        ldsm4t(x, a0 + s * 1024);
        ldsm4t(y, (a0 ^ 32) + s * 1024);
        const uint32_t b0 = lds32(bo + s * 32), b1 = lds32(bo + s * 32 + 16);
        mma16816(acc0, x[0], x[1], x[2], x[3], b0, b1);
        mma16816(acc1, y[0], y[1], y[2], y[3], b0, b1);
    }
    if (c == 0) {
        const uint32_t r = red + warp * 768 + g * 8;
        sts64f(r, acc0[0], acc0[1]); sts64f(r + 64, acc0[2], acc0[3]);
        sts64f(r + 128, acc1[0], acc1[1]); sts64f(r + 192, acc1[2], acc1[3]);
    }
}
__device__ __forceinline__ float red9(uint32_t red, int idx) {
    float v[9];
#pragma unroll
    for (int w = 0; w < 9; w++) v[w] = ldsf(red + w * 768 + idx * 4);
    return ((v[0] + v[1]) + (v[2] + v[3])) + ((v[4] + v[5]) + (v[6] + v[7])) + v[8];
}

__device__ __forceinline__ void ln_stats(uint32_t xa, uint32_t xb, uint32_t sh, uint32_t st, int warp, int lane, uint32_t& mean2, float& r0, float& r1) {
    const float s0 = bf_lo(sh), s1 = bf_hi(sh);
    const float a0 = bf_lo(xa) - s0, a1 = bf_hi(xa) - s1, b0 = bf_lo(xb) - s0, b1 = bf_hi(xb) - s1;
    float u0 = a0 + b0, u1 = a1 + b1, q0 = a0 * a0 + b0 * b0, q1 = a1 * a1 + b1 * b1;
#pragma unroll
    for (int o = 16; o > 0; o >>= 1) {
        u0 += __shfl_xor_sync(0xffffffffu, u0, o); u1 += __shfl_xor_sync(0xffffffffu, u1, o);
        q0 += __shfl_xor_sync(0xffffffffu, q0, o); q1 += __shfl_xor_sync(0xffffffffu, q1, o);
    }
    if (lane == 0) sts128(st + warp * 16, make_uint4(__float_as_uint(u0), __float_as_uint(u1), __float_as_uint(q0), __float_as_uint(q1)));
    csync();
    uint4 v[9];
#pragma unroll
    for (int w = 0; w < 9; w++) v[w] = lds128(st + w * 16);
#define SUM9(f) ((((__uint_as_float(v[0].f) + __uint_as_float(v[1].f)) + (__uint_as_float(v[2].f) + __uint_as_float(v[3].f))) + \
                  ((__uint_as_float(v[4].f) + __uint_as_float(v[5].f)) + (__uint_as_float(v[6].f) + __uint_as_float(v[7].f)))) + __uint_as_float(v[8].f))
    u0 = SUM9(x) * (1.0f / D_); u1 = SUM9(y) * (1.0f / D_);
    q0 = SUM9(z); q1 = SUM9(w);
#undef SUM9
    const uint32_t var2 = pack_bf(fmaxf(fmaf(q0, 1.0f / D_, -u0 * u0), 0.f), fmaxf(fmaf(q1, 1.0f / D_, -u1 * u1), 0.f));
    mean2 = pack_bf(u0 + s0, u1 + s1);
    const uint32_t ve2 = pack_bf(bf_lo(var2) + 1e-5f, bf_hi(var2) + 1e-5f);
    float d0, d1;
    asm("sqrt.approx.ftz.f32 %0, %1;" : "=f"(d0) : "f"(bf_lo(ve2)));
    asm("sqrt.approx.ftz.f32 %0, %1;" : "=f"(d1) : "f"(bf_hi(ve2)));
    const uint32_t sd2 = pack_bf(d0, d1);
    r0 = rcp(bf_lo(sd2)); r1 = rcp(bf_hi(sd2));
}
__device__ __forceinline__ uint32_t modulate2(uint32_t x, uint32_t mean2, float r0, float r1, uint32_t shift, uint32_t onepscale) {
    const uint32_t d = hsub2(x, mean2);
    const uint32_t y = pack_bf(bf_lo(d) * r0, bf_hi(d) * r1);
    return hadd2(hmul2(y, onepscale), shift);
}
constexpr uint32_t ONE2 = 0x3f803f80u;

__global__ void __launch_bounds__(NTHREADS, 1)
fused_block_kernel(const __grid_constant__ CUtensorMap tm_k, const __grid_constant__ CUtensorMap tm_v,
                   const __grid_constant__ CUtensorMap tm_wq, const __grid_constant__ CUtensorMap tm_wm,
                   const __grid_constant__ CUtensorMap tm_w1, const __grid_constant__ CUtensorMap tm_w3,
                   const __grid_constant__ CUtensorMap tm_w1x, const __grid_constant__ CUtensorMap tm_w3x,
                   const __nv_bfloat16* __restrict__ x, const __nv_bfloat16* __restrict__ wo, const __nv_bfloat16* __restrict__ w2,
                   const __nv_bfloat16* __restrict__ cvec, const __nv_bfloat16* __restrict__ wmod, __nv_bfloat16* __restrict__ out) {
    extern __shared__ __align__(1024) uint8_t smem[];
    int tid, cta;
    uint32_t sb;
    Scratch* gs;
    asm volatile("mov.u32 %0, %1;" : "=r"(tid) : "r"(threadIdx.x));
    asm volatile("mov.u32 %0, %1;" : "=r"(cta) : "r"(blockIdx.x));
    asm volatile("mov.u32 %0, %1;" : "=r"(sb) : "r"(smem_u32(smem)));
    asm volatile("mov.u64 %0, %1;" : "=l"(gs) : "l"(&g_s));
    const int warp = tid >> 5, lane = tid & 31;
    auto BAR = [&](int i) { return sb + SM_BAR + 8 * i; };

    const int bb = cta >> 6, kvh = (cta >> 2) & 15;
    const bool typeA = cta < 32;
    const int wj = cta - 32;
    const int nO = typeA ? 0 : (wj < 32 ? 2 : 3);
    const int o_r0 = wj < 32 ? 32 * wj : 1024 + 48 * (wj - 32);
    const bool m1 = cta < NM1CTA, m2 = cta >= NM1CTA && cta < NMODCTA;

    TS(0);
    const int krow0 = cta * KEYS_PER_CTA;
    uint64_t pol;
    asm volatile("createpolicy.fractional.L2::evict_first.b64 %0, 1.0;" : "=l"(pol));
    if (tid == NCT) {
        mbar_init(BAR(B_WQ), 1); mbar_init(BAR(B_WQ + 1), 1); mbar_init(BAR(B_KVFULL), 1);
        asm volatile("fence.mbarrier_init.release.cluster;" ::: "memory");
        TSL(22);
        mbar_expect_tx(BAR(B_WQ), 5 * BOX_BYTES);
#pragma unroll
        for (int i = 0; i < 5; i++) tma2d(sb + SM_XB + (i < 4 ? i : 8) * BOX_BYTES, &tm_wq, cta * 32, (i < 4 ? i : 8) * 64, BAR(B_WQ), pol);
        mbar_expect_tx(BAR(B_WQ + 1), 4 * BOX_BYTES);
#pragma unroll
        for (int i = 4; i < 8; i++) tma2d(sb + SM_XB + i * BOX_BYTES, &tm_wq, cta * 32, i * 64, BAR(B_WQ + 1), pol);
        mbar_expect_tx(BAR(B_KVFULL), TILE_BYTES);
        tma2d(sb + SM_RING, &tm_k, 0, krow0, BAR(B_KVFULL), pol);
        tma2d(sb + SM_RING + 8192, &tm_k, 64, krow0, BAR(B_KVFULL), pol);
#pragma unroll
        for (int i = 1; i < 8; i++) mbar_init(BAR(B_KVFULL + i), 1);
#pragma unroll
        for (int i = 0; i < 8; i++) mbar_init(BAR(B_KVEMPTY + i), 8);
        mbar_init(BAR(B_WM), 1); mbar_init(BAR(B_WM + 1), 1);
#pragma unroll
        for (int i = B_W1; i <= B_MID; i++) mbar_init(BAR(i), 1);
        mbar_init(BAR(B_XFREE), NCW); mbar_init(BAR(B_FAC), 1);
        asm volatile("fence.mbarrier_init.release.cluster;" ::: "memory");
    }
    if (m1 && warp < NCW) {
        const int g = lane >> 2, c = lane & 3;
        const char* src = reinterpret_cast<const char*>(wmod) + (size_t)(warp * 64 + g) * (NMOD * 2) + (c & 1) * (D_ * 2) + cta * 32 + (c >> 1) * 16;
        const uint32_t dst = sb + SM_XA + (warp * 64 + g) * 64 + ((c ^ ((g >> 1) & 3)) << 4);
#pragma unroll
        for (int i = 0; i < 8; i++) cp16(dst + i * 512, src + (size_t)i * 8 * (NMOD * 2));
    }
    if (warp == NCW) {
        __syncwarp();
        asm volatile("bar.arrive 0, 320;" ::: "memory");
        if (lane != 0) return;
        const uint32_t hist = sb + SM_HIST;
        sts32(hist, BAR(B_WQ)); sts32(hist + 4, BAR(B_WQ + 1)); sts32(hist + 8, BAR(B_KVFULL));
        int n = 3;
        auto window = [&](int D) {
            if (n >= D) { const uint32_t h = lds32(hist + ((n - D) & 15) * 4); mbar_wait(h & ~1u, h & 1u); }
        };
        auto issued = [&](uint32_t bar, uint32_t par) { sts32(hist + (n & 15) * 4, bar | par); n++; };
        auto plane_half = [&](const CUtensorMap* map, uint32_t base, uint32_t box8, int bar, int half, int D) {
            window(D);
            mbar_expect_tx(BAR(bar + half), (half ? 4 : 5) * BOX_BYTES);
#pragma unroll
            for (int i = 0; i < 4; i++) tma2d(base + (half * 4 + i) * BOX_BYTES, map, cta * 32, (half * 4 + i) * 64, BAR(bar + half), pol);
            if (!half) tma2d(box8, map, cta * 32, 512, BAR(bar), pol);
            issued(BAR(bar + half), 0);
        };
        auto rows8 = [&](const __nv_bfloat16* w, int row0, int rpg, uint32_t base, uint32_t g7, uint32_t bar, int g0, int ng) {
            const uint32_t gb = rpg * ROWB;
#pragma unroll 1
            for (int gi = g0; gi < g0 + ng; gi++)
                bulk_g2s(gi < 7 ? base + gi * (gb + 16) : g7, reinterpret_cast<const char*>(w) + (size_t)row0 * ROWB + (size_t)gi * gb, gb, bar, pol);
        };
        uint32_t pbase;
        asm volatile("ld.relaxed.gpu.global.u32 %0, [%1];" : "=r"(pbase) : "l"(&gs->epoch) : "memory");
        uint32_t pcnt = 0;
        int Dbulk = TUNE_DB;
#pragma unroll 1
        for (int j = 1; j < NITEMS; j++) {
            const int s = j & 7;
            if ((j & 3) == 1) {
                if (j >= 8) {
                    const int extra = (m2 && j - 4 <= TUNE_JM2 ? 2 : 0) + (j - 4 <= TUNE_JMID ? (typeA ? 3 : nO) : 0);
                    const int avgx = (j - 4 <= TUNE_JM2 ? 144 : 0) + (j - 4 <= TUNE_JMID ? 352 : 0);
                    const int lead = (j - 5 - extra) * NCTA + avgx + TUNE_PACE_BIAS - (int)(pcnt - pbase * (uint32_t)(NCTA * NITEMS));
                    Dbulk = lead > TUNE_PACE_TH ? (lead > 3 * TUNE_PACE_TH ? TUNE_DB - TUNE_PACE_DN : TUNE_DB - 1) : (lead < -TUNE_PACE_TH ? (lead < -3 * TUNE_PACE_TH ? TUNE_DB + TUNE_PACE_UP : TUNE_DB + 1) : TUNE_DB);
                }
                asm volatile("atom.relaxed.gpu.global.add.u32 %0, [%1], 4;" : "=r"(pcnt) : "l"(&gs->prog) : "memory");
            }
            int D = Dbulk;
            if (j >= 8) mbar_wait(BAR(B_KVEMPTY + s), ((j >> 3) - 1) & 1);
            else if (!mbar_test(BAR(B_KVEMPTY), 0)) D = TUNE_DH;
            if (j >= TUNE_JTAIL) D = TUNE_DT;
            window(D);
            mbar_expect_tx(BAR(B_KVFULL + s), TILE_BYTES);
            const CUtensorMap* map = j < NTILES ? &tm_k : &tm_v;
            tma2d(sb + SM_RING + s * TILE_BYTES, map, 0, krow0 + (j & 31) * TILE_KEYS, BAR(B_KVFULL + s), pol);
            tma2d(sb + SM_RING + s * TILE_BYTES + 8192, map, 64, krow0 + (j & 31) * TILE_KEYS, BAR(B_KVFULL + s), pol);
            issued(BAR(B_KVFULL + s), (j >> 3) & 1);
            if (m2 && (j == TUNE_JM2 || j == TUNE_JM2 + 1)) plane_half(&tm_wm, sb + SM_XA, sb + SM_XA + 8 * BOX_BYTES, B_WM, j - TUNE_JM2, D);
            if (j >= TUNE_JMID && j < TUNE_JMID + 6 && !(j & 1)) {
                const int k = (j - TUNE_JMID) >> 1;
                if (k == 0) {
                    mbar_wait(BAR(B_XFREE), 0);
                    mbar_expect_tx(BAR(B_MID), typeA ? 48 * ROWB : 16 * nO * ROWB);
                }
                if (typeA) {
                    if (k < 2) {
#pragma unroll
                        for (int i = 0; i < 3; i++) tma2d(sb + SM_XA + k * 18432 + i * 6144, k ? &tm_w3x : &tm_w1x, NQ + 16 * cta, i * 192, BAR(B_MID), pol);
                    } else rows8(w2, NQ + 16 * cta, 2, sb + SM_XW2E, sb + SM_XW2E + 7 * (2 * ROWB + 16), BAR(B_MID), 0, 8);
                } else {
                    rows8(wo, o_r0, 2 * nO, sb + SM_X, sb + SM_X + 7 * (2 * nO * ROWB + 16), BAR(B_MID), 3 * k, k < 2 ? 3 : 2);
                }
            }
        }
        TSL(16);
#pragma unroll 1
        for (int i = 0; i < 4; i++) {
            const int m3 = i & 1, h = i >> 1;
            mbar_wait(BAR(B_KVEMPTY + 2 * m3 + h), 1);
            plane_half(m3 ? &tm_w3 : &tm_w1, sb + (m3 ? SM_W3 : SM_W1), sb + (m3 ? SM_W3B8 : SM_W1B8), m3 ? B_W3 : B_W1, h, TUNE_DT);
        }
        mbar_wait(BAR(B_KVEMPTY + 4), 1);
        mbar_wait(BAR(B_KVEMPTY + 5), 1);
#pragma unroll 1
        for (int h = 0; h < 2; h++) {
            window(TUNE_DT);
            mbar_expect_tx(BAR(B_W2 + h), 16 * ROWB);
            rows8(w2, cta * 32, 4, sb + SM_W2, sb + SM_W2G7, BAR(B_W2 + h), 4 * h, 4);
            issued(BAR(B_W2 + h), 0);
        }
        TSL(17);
        return;
    }

    const int g = lane >> 2, c = lane & 3, mi = lane >> 3, kap = lane & 7;
    const int whalf = (warp >> 2) & 1;
    const int rowl = kap + 8 * (mi >> 1);
    const uint32_t sw64 = (rowl >> 1) & 3;
    const uint32_t hbo = sb + SM_HB + (g & 1) * (HSTRIDE * 2) + warp * 128 + c * 4;
    const uint32_t redw = sb + SM_RED + warp * 768 + g * 8;
    const uint32_t* x32 = reinterpret_cast<const uint32_t*>(x);
    const unsigned short* x16 = reinterpret_cast<const unsigned short*>(x);
    uint32_t tag;
    asm volatile("ld.relaxed.gpu.global.u32 %0, [%1];" : "=r"(tag) : "l"(&gs->epoch) : "memory");
    if (cta < NMODCTA) {
        const uint32_t* c32 = reinterpret_cast<const uint32_t*>(cvec);
        const uint32_t c0 = __ldg(c32 + tid), c1 = __ldg(c32 + D_ / 2 + tid);
        uint32_t u0 = 0, u1 = 0, z0 = 0, z1 = 0, xo = 0;
        if (m1) {
            u0 = __ldg(x32 + tid); u1 = __ldg(x32 + D_ / 2 + tid);
            z0 = __ldg(x32); z1 = __ldg(x32 + D_ / 2);
            const int col = cta * 16 + (lane >> 1);
            xo = (uint32_t)__ldg(x16 + col) | ((uint32_t)__ldg(x16 + D_ + col) << 16);
        }
        sts32(sb + SM_SC + tid * 4, pack_bf(silu_f(bf_lo(c0)), silu_f(bf_hi(c0))));
        sts32(sb + SM_SC + HSTRIDE * 2 + tid * 4, pack_bf(silu_f(bf_lo(c1)), silu_f(bf_hi(c1))));
        if (m1) {
            uint32_t mean2; float r0, r1;
            ln_stats(__byte_perm(u0, u1, 0x5410), __byte_perm(u0, u1, 0x7632), __byte_perm(z0, z1, 0x5410), sb + SM_ST, warp, lane, mean2, r0, r1);
            asm volatile("cp.async.wait_all;" ::: "memory");
            __syncwarp();
            TSL(70 + warp);
            plane_gemv(sb + SM_XA, sb + SM_SC, sb + SM_RED, warp, lane);
            csync();
            if (warp == 0) {
                const int idx = (lane >> 4) * 32 + (lane & 15);
                const float sa = red9(sb + SM_RED, idx), ca = red9(sb + SM_RED, idx + 16);
                const uint32_t sa2 = pack_bf(sa, __shfl_xor_sync(0xffffffffu, sa, 1)), ca2 = pack_bf(ca, __shfl_xor_sync(0xffffffffu, ca, 1));
                const uint32_t h = modulate2(xo, mean2, r0, r1, sa2, hadd2(ca2, ONE2));
                const uint32_t hp = __shfl_sync(0xffffffffu, h, (lane & 7) * 4), hq = __shfl_sync(0xffffffffu, h, (lane & 7) * 4 + 2);
                st_pkt2(&gs->h1[lane >> 3][cta * 16 + (lane & 7) * 2], hp, hq, tag + 1);
            }
            TS(2);
        }
    }
    tag += 1;
    asm volatile("bar.sync 0, 320;" ::: "memory");
    TS(1);
    {
        uint32_t af[4][2][4];
        const uint32_t a0 = sb + SM_XB + warp * BOX_BYTES + rowl * 64 + (((mi & 1) ^ sw64) << 4);
        mbar_wait(BAR(B_WQ + whalf), 0);
        TS(21);
#pragma unroll
        for (int s = 0; s < 4; s++) { ldsm4t(af[s][0], a0 + s * 1024); ldsm4t(af[s][1], (a0 ^ 32) + s * 1024); }
        uint32_t ha[1], hb[1];
        pollN<1>(&gs->h1[cta & 3][2 * tid], 0, tag, ha, hb);
        sts32(sb + SM_HB + tid * 4, __byte_perm(ha[0], hb[0], 0x5410));
        sts32(sb + SM_HB + HSTRIDE * 2 + tid * 4, __byte_perm(ha[0], hb[0], 0x7632));
        __syncwarp();
        TS(3);
        float acc0[4] = {0.f, 0.f, 0.f, 0.f}, acc1[4] = {0.f, 0.f, 0.f, 0.f};
#pragma unroll
        for (int s = 0; s < 4; s++) {
            const uint32_t b0 = lds32(hbo + s * 32), b1 = lds32(hbo + s * 32 + 16);
            mma16816(acc0, af[s][0][0], af[s][0][1], af[s][0][2], af[s][0][3], b0, b1);
            mma16816(acc1, af[s][1][0], af[s][1][1], af[s][1][2], af[s][1][3], b0, b1);
        }
        if (c == 0) {
            sts64f(redw, acc0[0], acc0[1]); sts64f(redw + 64, acc0[2], acc0[3]);
            sts64f(redw + 128, acc1[0], acc1[1]); sts64f(redw + 192, acc1[2], acc1[3]);
        }
        csync();
        if (warp == 0) {
            const int idx = (lane & 15) * 4 + (lane >> 4);
            st_pkt(&gs->q[lane >> 4][cta * 16 + (lane & 15)], pack_bf(red9(sb + SM_RED, idx), red9(sb + SM_RED, idx + 2)), tag);
        }
    }
    TS(4);
    auto mod2_phase = [&]() {
        if (m2) {
            mbar_wait(BAR(B_WM + whalf), 0);
            plane_gemv(sb + SM_XA, sb + SM_SC, sb + SM_RED, warp, lane);
            csync();
            if (tid < 64) {
                const float v = red9(sb + SM_RED, tid);
                const float o = __shfl_xor_sync(0xffffffffu, v, 1);
                const int which = cta / 18, i = (cta % 18) * 32 + (tid >> 1);
                if ((tid & 1) == 0) st_pkt(&gs->mod[(which == 2 || which == 5) ? 1 : 0][i][which >> 2], pack_bf(v, o), tag);
            }
        }
        asm volatile("fence.proxy.async.shared::cta;" ::: "memory");
        __syncwarp();
        if (lane == 0) mbar_arrive(BAR(B_XFREE));
    };

    const bool reducer = cta < NRED_CTA;
    const int rcol = cta * 8 + (lane & 3) * 2;
    uint32_t gav[2] = {0, 0}, gbv[2] = {0, 0}, xin[2] = {0, 0};
    uint32_t wof[4][3][4];
    auto preload_tail = [&]() {
        if (nO > 0) {
            const uint32_t ab = sb + SM_X + kap * (2 * nO * ROWB + 16) + (mi >> 1) * ROWB + (mi & 1) * 16 + warp * 128;
            mbar_wait(BAR(B_MID), 0);
#pragma unroll
            for (int i = 0; i < 4; i++) {
                ldsm4t(wof[i][0], ab + i * 32);
                ldsm4t(wof[i][1], ab + i * 32 + 2 * ROWB);
                ldsm4t(wof[i][2], ab + i * 32 + 4 * ROWB);
            }
        }
        if (reducer && warp == 0) {
            const uint32_t u0 = __ldg(x32 + (rcol >> 1)), u1 = __ldg(x32 + ((D_ + rcol) >> 1));
            xin[0] = __byte_perm(u0, u1, 0x5410); xin[1] = __byte_perm(u0, u1, 0x7632);
            pollN<2>(&gs->mod[1][rcol][0], 2, tag, gav, gbv);
        }
    };

    if (warp == 8) {
#pragma unroll 2
        for (int i = lane; i < D_; i += 32) {
            st_pkt2(&gs->p4[cta][i][0], 0u, 0u, 0u);
            if (!typeA) st_pkt2(&gs->p2[wj][i][0], 0u, 0u, 0u);
            if (i < DH) st_pkt2(&gs->o[cta][0][0][0][0] + 2 * i, 0u, 0u, 0u);
        }
        asm volatile("bar.sync 3, 64;" ::: "memory");
        mod2_phase();
#pragma unroll 1
        for (int i = lane; i < D_; i += 64) {
            uint32_t s2[2], c2[2];
            pollN<2>(&gs->mod[0][i][0], 64, tag, s2, c2);
            sts64(sb + SM_MB + i * 8, s2[0], hadd2(c2[0], ONE2));
            sts64(sb + SM_MB + (i + 32) * 8, s2[1], hadd2(c2[1], ONE2));
        }
        {
            uint32_t a[1], e[1];
            pollN<1>(&gs->ml[(cta & ~3) + ((lane >> 1) & 3)][(lane & 1) * 2], 0, tag, a, e);
            const float m = __uint_as_float(a[0]);
            float M = fmaxf(m, __shfl_xor_sync(0xffffffffu, m, 2));
            M = fmaxf(M, __shfl_xor_sync(0xffffffffu, M, 4));
            const float w = ex2((m - M) * LOG2E);
            float L = w * __uint_as_float(e[0]);
            L += __shfl_xor_sync(0xffffffffu, L, 2);
            L += __shfl_xor_sync(0xffffffffu, L, 4);
            if ((lane >> 1) == (cta & 3)) sts32(sb + SM_FAC + (lane & 1) * 4, __float_as_uint(w / L));
        }
        __syncwarp();
        if (lane == 0) mbar_arrive(BAR(B_FAC));
        preload_tail();
    } else {
        if (tid < 64) {
            uint32_t a[1], e[1];
            pollN<1>(&gs->q[bb][kvh * 128 + tid * 2], 0, tag, a, e);
            sts64(sb + SM_QS + (tid >> 5) * (QSTRIDE * 2) + (tid & 31) * 8, a[0], e[0]);
        }
        async8();
        if (warp == 7) asm volatile("bar.arrive 3, 64;" ::: "memory");
        TS(5);
        uint32_t qa[8][2];
#pragma unroll
        for (int s = 0; s < 8; s++) {
            const uint32_t a = sb + SM_QS + (g & 1) * (QSTRIDE * 2) + (16 * s + 2 * c) * 2;
            qa[s][0] = lds32(a); qa[s][1] = lds32(a + 16);
        }
        constexpr float SCALE = 0.08838834764831845f;
        float mrun = -INFINITY;
        const uint32_t koff = (8 * warp + kap) * 128 + ((mi ^ kap) << 4);
        const uint32_t spw = sb + SM_SP + (g & 1) * 128 + c * 32;
#pragma unroll 1
        for (int t = 0; t < NTILES; t++) {
            const int s = t & 7;
            mbar_wait(BAR(B_KVFULL + s), (t >> 3) & 1);
            if ((t & 3) == 0) TS(24 + (t >> 2));
            float s0[4] = {0.f, 0.f, 0.f, 0.f}, s1[4] = {0.f, 0.f, 0.f, 0.f};
            const uint32_t ka = sb + SM_RING + s * TILE_BYTES + koff;
#pragma unroll
            for (int i = 0; i < 4; i++) {
                uint32_t u[4];
                ldsm4(u, (ka ^ ((i & 1) << 6)) + (i >> 1) * 8192);
                mma16816(s0, qa[2 * i][0], 0u, qa[2 * i][1], 0u, u[0], u[1]);
                mma16816(s1, qa[2 * i + 1][0], 0u, qa[2 * i + 1][1], 0u, u[2], u[3]);
            }
            __syncwarp();
            if (lane == 0) mbar_arrive(BAR(B_KVEMPTY + s));
            const uint32_t d0 = pack_bf(s0[0] + s1[0], s0[1] + s1[1]);
            const uint32_t e0 = pack_bf(bf_lo(d0) * SCALE, bf_hi(d0) * SCALE);
            mrun = fmaxf(mrun, fmaxf(bf_lo(e0), bf_hi(e0)));
            if (g < 2) sts32(spw + t * 256 + warp * 4, e0);
        }
        TS(6);
        mrun = fmaxf(mrun, __shfl_xor_sync(0xffffffffu, mrun, 1));
        mrun = fmaxf(mrun, __shfl_xor_sync(0xffffffffu, mrun, 2));
        if (lane == 0 || lane == 4) sts32(sb + SM_ST + (g * 8 + warp) * 4, __float_as_uint(mrun));
        async8();
        {
            const int h = (tid >> 2) & 1;
            const uint4 m0 = lds128(sb + SM_ST + h * 32), m1v = lds128(sb + SM_ST + h * 32 + 16);
            const float M = fmaxf(fmaxf(fmaxf(__uint_as_float(m0.x), __uint_as_float(m0.y)), fmaxf(__uint_as_float(m0.z), __uint_as_float(m0.w))),
                                  fmaxf(fmaxf(__uint_as_float(m1v.x), __uint_as_float(m1v.y)), fmaxf(__uint_as_float(m1v.z), __uint_as_float(m1v.w))));
            const float Ms = M * LOG2E;
            float l = 0.f;
#pragma unroll
            for (int k = 0; k < 2; k++) {
                uint4 v = lds128(sb + SM_SP + tid * 32 + k * 16);
                uint32_t* w = reinterpret_cast<uint32_t*>(&v);
#pragma unroll
                for (int i = 0; i < 4; i++) {
                    const float p0 = ex2(fmaf(bf_lo(w[i]), LOG2E, -Ms)), p1 = ex2(fmaf(bf_hi(w[i]), LOG2E, -Ms));
                    l += p0 + p1;
                    w[i] = pack_bf(p0, p1);
                }
                sts128(sb + SM_SP + tid * 32 + k * 16, v);
            }
            l += __shfl_xor_sync(0xffffffffu, l, 1); l += __shfl_xor_sync(0xffffffffu, l, 2);
            l += __shfl_xor_sync(0xffffffffu, l, 8); l += __shfl_xor_sync(0xffffffffu, l, 16);
            if (lane == 0 || lane == 4) sts32(sb + SM_ST + 64 + (h * 8 + warp) * 4, __float_as_uint(l));
            async8();
            if (tid == 0 || tid == 4) {
                const uint4 l0 = lds128(sb + SM_ST + 64 + h * 32), l1 = lds128(sb + SM_ST + 64 + h * 32 + 16);
                const float L = ((__uint_as_float(l0.x) + __uint_as_float(l0.y)) + (__uint_as_float(l0.z) + __uint_as_float(l0.w))) +
                                ((__uint_as_float(l1.x) + __uint_as_float(l1.y)) + (__uint_as_float(l1.z) + __uint_as_float(l1.w)));
                st_pkt2(&gs->ml[cta][h * 2], __float_as_uint(M), __float_as_uint(L), tag);
            }
            __syncwarp();
        }
        mod2_phase();
        TS(7);
        float oacc0[4] = {0.f, 0.f, 0.f, 0.f}, oacc1[4] = {0.f, 0.f, 0.f, 0.f};
        float f0 = 0.f, f1 = 0.f;
        const uint32_t voff = (warp >> 2) * 8192 + rowl * 128 + (((2 * (warp & 3) + (mi & 1)) ^ kap) << 4);
        const u64* odst = &gs->o[cta][0][warp][g][0];
#pragma unroll 1
        for (int t = 0; t < NTILES; t++) {
            const int s = t & 7;
            uint4 pb[2];
            pb[0] = lds128(spw + t * 256); pb[1] = lds128(spw + t * 256 + 16);
            mbar_wait(BAR(B_KVFULL + s), (t >> 3) & 1);
            if ((t & 3) == 3) TS(32 + (t >> 2));
            const uint32_t va = sb + SM_RING + s * TILE_BYTES + voff;
#pragma unroll
            for (int i = 0; i < 2; i++) {
                uint32_t u[4], v[4];
                ldsm4t(u, va + (2 * i) * 2048);
                ldsm4t(v, va + (2 * i + 1) * 2048);
                mma16816(oacc0, u[0], u[1], u[2], u[3], pb[i].x, pb[i].y);
                mma16816(oacc1, v[0], v[1], v[2], v[3], pb[i].z, pb[i].w);
            }
            __syncwarp();
            if (lane == 0) mbar_arrive(BAR(B_KVEMPTY + s));
            if (t == TUNE_PRE) {
                preload_tail();
                mbar_wait(BAR(B_FAC), 0);
                f0 = ldsf(sb + SM_FAC); f1 = ldsf(sb + SM_FAC + 4);
            }
        }
        TS(8);
        st_pkt2_if<0>(c == 0, odst, (oacc0[0] + oacc1[0]) * f0, (oacc0[2] + oacc1[2]) * f0, tag);
        st_pkt2_if<DH * 8>(c == 0, odst, (oacc0[1] + oacc1[1]) * f1, (oacc0[3] + oacc1[3]) * f1, tag);
    }
    TS(9);
    const uint32_t vpb = sb + SM_VP + (g & 1) * (VPSTRIDE * 2) + c * 4;
    if (nO > 0) {
        const int j = lane & 7, s = (lane >> 3) & 3, b = warp & 1, u = warp >> 1;
        const u64* dst = &gs->p2[wj][warp * 64 + g][0];
        if (u < nO) {
            const int row = o_r0 + 16 * u;
            const int hq = row >> 7;
            const int r = 16 * u + j + 8 * (s & 1);
            const int grp = nO == 3 ? (r * 43) >> 8 : r >> 2, rr = r - grp * 2 * nO;
            const uint32_t vd = sb + SM_VP + b * (VPSTRIDE * 2) + (16 * (rr >> 1) + (rr & 1) * 8 + grp) * 2;
            uint32_t a[1], e[1];
            pollN<1>(&gs->o[b * 64 + (hq >> 1) * 4 + s][hq & 1][(row >> 4) & 7][j][0], 0, tag, a, e);
            float o0 = __uint_as_float(a[0]), o1 = __uint_as_float(e[0]);
            o0 += __shfl_xor_sync(0xffffffffu, o0, 8); o1 += __shfl_xor_sync(0xffffffffu, o1, 8);
            o0 += __shfl_xor_sync(0xffffffffu, o0, 16); o1 += __shfl_xor_sync(0xffffffffu, o1, 16);
            const uint32_t pk = pack_bf(o0, o1);
            if (s < 2) asm volatile("st.shared.b16 [%0], %1;" ::"r"(vd), "h"((unsigned short)(s ? pk >> 16 : pk)) : "memory");
        }
        csync();
        TS(10);
        uint32_t b0[3], b1[3];
#pragma unroll
        for (int k = 0; k < 3; k++) { b0[k] = lds32(vpb + k * 32); b1[k] = lds32(vpb + k * 32 + 16); }
        float acc[4][4];
#pragma unroll
        for (int i = 0; i < 4; i++) { acc[i][0] = acc[i][1] = acc[i][2] = acc[i][3] = 0.f; mma16816(acc[i], wof[i][0][0], wof[i][0][1], wof[i][0][2], wof[i][0][3], b0[0], b1[0]); }
#pragma unroll
        for (int i = 0; i < 4; i++) mma16816(acc[i], wof[i][1][0], wof[i][1][1], wof[i][1][2], wof[i][1][3], b0[1], b1[1]);
        if (nO == 3) {
#pragma unroll
            for (int i = 0; i < 4; i++) mma16816(acc[i], wof[i][2][0], wof[i][2][1], wof[i][2][2], wof[i][2][3], b0[2], b1[2]);
        }
        constexpr int CP = 32;
        st_pkt2_if<0 * CP>(c == 0, dst, acc[0][0], acc[0][1], tag);  st_pkt2_if<4 * CP>(c == 0, dst, acc[0][2], acc[0][3], tag);
        st_pkt2_if<8 * CP>(c == 0, dst, acc[1][0], acc[1][1], tag);  st_pkt2_if<12 * CP>(c == 0, dst, acc[1][2], acc[1][3], tag);
        st_pkt2_if<16 * CP>(c == 0, dst, acc[2][0], acc[2][1], tag); st_pkt2_if<20 * CP>(c == 0, dst, acc[2][2], acc[2][3], tag);
        st_pkt2_if<24 * CP>(c == 0, dst, acc[3][0], acc[3][1], tag); st_pkt2_if<28 * CP>(c == 0, dst, acc[3][2], acc[3][3], tag);
    }
    TS(11);
    uint32_t x1v[2] = {0, 0};
    auto sum8 = [&](uint32_t (&r)[2]) {
        float v[4] = {0.f, 0.f, 0.f, 0.f}, w[4] = {0.f, 0.f, 0.f, 0.f};
#pragma unroll
        for (int k = 0; k < 8; k += 2) {
            const uint4 a = lds128(sb + SM_SP + k * 64 + (lane & 3) * 16), e = lds128(sb + SM_SP + k * 64 + 64 + (lane & 3) * 16);
            v[0] += __uint_as_float(a.x); v[1] += __uint_as_float(a.y); v[2] += __uint_as_float(a.z); v[3] += __uint_as_float(a.w);
            w[0] += __uint_as_float(e.x); w[1] += __uint_as_float(e.y); w[2] += __uint_as_float(e.z); w[3] += __uint_as_float(e.w);
        }
        r[0] = pack_bf(v[0] + w[0], v[1] + w[1]); r[1] = pack_bf(v[2] + w[2], v[3] + w[3]);
    };
    if (reducer && warp < 8) {
        uint32_t a[3], e[3];
        pollN<3>(&gs->p2[warp * 12 + (lane >> 3)][cta * 8 + (lane & 7)][0], 4 * D_ * 2, tag, a, e);
        float v0 = (__uint_as_float(a[0]) + __uint_as_float(a[1])) + __uint_as_float(a[2]);
        float v1 = (__uint_as_float(e[0]) + __uint_as_float(e[1])) + __uint_as_float(e[2]);
        v0 += __shfl_xor_sync(0xffffffffu, v0, 8); v1 += __shfl_xor_sync(0xffffffffu, v1, 8);
        v0 += __shfl_xor_sync(0xffffffffu, v0, 16); v1 += __shfl_xor_sync(0xffffffffu, v1, 16);
        if (lane < 8) sts64f(sb + SM_SP + warp * 64 + lane * 8, v0, v1);
        if (warp == 0) {
            async8();
            uint32_t r[2];
            sum8(r);
            x1v[0] = hadd2(xin[0], hmul2(gav[0], r[0])); x1v[1] = hadd2(xin[1], hmul2(gav[1], r[1]));
            if (lane < 16) st_pkt2(&gs->x1[lane >> 2][cta][(lane & 3) * 2], x1v[0], x1v[1], tag);
            __syncwarp();
        } else {
            asm volatile("bar.arrive 2, 256;" ::: "memory");
        }
    }
    TSL(60 + warp);
    {
        const uint32_t pb = ((mi & 1) ? (warp < 8 ? sb + SM_W3 + warp * BOX_BYTES : sb + SM_W3B8)
                                      : (warp < 8 ? sb + SM_W1 + warp * BOX_BYTES : sb + SM_W1B8)) + rowl * 64 + (sw64 << 4);
        const uint32_t pe = sb + SM_XA + (mi & 1) * 18432 + (warp * 64 + rowl) * 32 + (((rowl >> 2) & 1) << 4);
        const uint32_t ab = (kap < 7 ? sb + SM_W2 + kap * (4 * ROWB + 16) : sb + SM_W2G7) + (mi >> 1) * ROWB + (mi & 1) * 16 + warp * 128;
        const uint32_t aeb = sb + SM_XW2E + kap * (2 * ROWB + 16) + (mi >> 1) * ROWB + (mi & 1) * 16 + warp * 128;
        const u64* dst = &gs->p4[cta][warp * 64 + g][0];
        const int ar = tid >> 1;
        const uint32_t ared = sb + SM_RED + ((ar >> 3) * 32 + (ar & 7) * 2 + (tid & 1)) * 4;
        const uint32_t avp = sb + SM_VP + (tid & 1) * (VPSTRIDE * 2) +
                             (ar < 32 ? 16 * ((ar & 3) >> 1) + (ar & 1) * 8 + (ar >> 2) : 32 + (ar & 1) * 8 + ((ar - 32) >> 1)) * 2;
        uint32_t af[4][4][4], ae[4][2][4], wf[4][3][4];
        if (typeA) {
            mbar_wait(BAR(B_MID), 0);
#pragma unroll
            for (int s = 0; s < 4; s++) { ldsm4t(ae[s][0], pe + s * 512); ldsm4t(ae[s][1], (pe ^ 16) + s * 512); ldsm4t(wf[s][2], aeb + s * 32); }
        }
        const uint4 mb = lds128(sb + SM_MB + tid * 16);
        mbar_wait(BAR(B_W1 + whalf), 0);
        mbar_wait(BAR(B_W3 + whalf), 0);
#pragma unroll
        for (int s = 0; s < 4; s++)
#pragma unroll
            for (int j = 0; j < 4; j++) ldsm4t(af[s][j], (pb ^ (j << 4)) + s * 1024);
        TSL(40 + warp);
        uint32_t a[2], e[2];
        pollN<2>(&gs->x1[cta & 3][tid >> 2][(tid & 3) * 2], -((tid >> 2) * 16 + (tid & 3) * 2), tag, a, e);
        TSL(50 + warp);
        uint32_t mean2; float r0, r1;
        ln_stats(a[0], e[0], a[1], sb + SM_ST, warp, lane, mean2, r0, r1);
        const uint32_t ha = modulate2(a[0], mean2, r0, r1, mb.x, mb.y);
        const uint32_t hb = modulate2(e[0], mean2, r0, r1, mb.z, mb.w);
        sts32(sb + SM_HB + tid * 4, __byte_perm(ha, hb, 0x5410));
        sts32(sb + SM_HB + HSTRIDE * 2 + tid * 4, __byte_perm(ha, hb, 0x7632));
        __syncwarp();
        float acc[6][4];
#pragma unroll
        for (int j = 0; j < 6; j++) acc[j][0] = acc[j][1] = acc[j][2] = acc[j][3] = 0.f;
#pragma unroll
        for (int s = 0; s < 4; s++) {
            const uint32_t b0 = lds32(hbo + s * 32), b1 = lds32(hbo + s * 32 + 16);
#pragma unroll
            for (int j = 0; j < 4; j++) mma16816(acc[j], af[s][j][0], af[s][j][1], af[s][j][2], af[s][j][3], b0, b1);
            if (typeA) {
                mma16816(acc[4], ae[s][0][0], ae[s][0][1], ae[s][0][2], ae[s][0][3], b0, b1);
                mma16816(acc[5], ae[s][1][0], ae[s][1][1], ae[s][1][2], ae[s][1][3], b0, b1);
            }
        }
        if (c == 0) {
#pragma unroll
            for (int j = 0; j < 6; j++) { sts64f(redw + j * 128, acc[j][0], acc[j][1]); sts64f(redw + j * 128 + 64, acc[j][2], acc[j][3]); }
        }
        TS(15);
        csync();
        if (tid < (typeA ? 96 : 64)) {
            const uint32_t gu = pack_bf(red9(ared, 0), red9(ared, 16));
            const uint32_t sg = pack_bf(silu_f(bf_lo(gu)), 0.f);
            const uint32_t hh = hmul2(sg, gu >> 16);
            asm volatile("st.shared.b16 [%0], %1;" ::"r"(avp), "h"((unsigned short)hh) : "memory");
        }
        mbar_wait(BAR(B_W2), 0);
        mbar_wait(BAR(B_W2 + 1), 0);
#pragma unroll
        for (int i = 0; i < 4; i++) { ldsm4t(wf[i][0], ab + i * 32); ldsm4t(wf[i][1], ab + i * 32 + 2 * ROWB); }
        csync();
        TS(18);
        uint32_t b0[3], b1[3];
#pragma unroll
        for (int k = 0; k < 3; k++) { b0[k] = lds32(vpb + k * 32); b1[k] = lds32(vpb + k * 32 + 16); }
        float o[4][4];
#pragma unroll
        for (int i = 0; i < 4; i++) { o[i][0] = o[i][1] = o[i][2] = o[i][3] = 0.f; mma16816(o[i], wf[i][0][0], wf[i][0][1], wf[i][0][2], wf[i][0][3], b0[0], b1[0]); }
#pragma unroll
        for (int i = 0; i < 4; i++) mma16816(o[i], wf[i][1][0], wf[i][1][1], wf[i][1][2], wf[i][1][3], b0[1], b1[1]);
        if (typeA) {
#pragma unroll
            for (int i = 0; i < 4; i++) mma16816(o[i], wf[i][2][0], wf[i][2][1], wf[i][2][2], wf[i][2][3], b0[2], b1[2]);
        }
        constexpr int CP = 32;
        st_pkt2_if<0 * CP>(c == 0, dst, o[0][0], o[0][1], tag);  st_pkt2_if<4 * CP>(c == 0, dst, o[0][2], o[0][3], tag);
        st_pkt2_if<8 * CP>(c == 0, dst, o[1][0], o[1][1], tag);  st_pkt2_if<12 * CP>(c == 0, dst, o[1][2], o[1][3], tag);
        st_pkt2_if<16 * CP>(c == 0, dst, o[2][0], o[2][1], tag); st_pkt2_if<20 * CP>(c == 0, dst, o[2][2], o[2][3], tag);
        st_pkt2_if<24 * CP>(c == 0, dst, o[3][0], o[3][1], tag); st_pkt2_if<28 * CP>(c == 0, dst, o[3][2], o[3][3], tag);
    }
    TS(19);
    if (reducer && warp < 8) {
        uint32_t a[4], e[4];
        pollN<4>(&gs->p4[warp * 16 + (lane >> 3)][cta * 8 + (lane & 7)][0], 4 * D_ * 2, tag, a, e);
        float v0 = (__uint_as_float(a[0]) + __uint_as_float(a[1])) + (__uint_as_float(a[2]) + __uint_as_float(a[3]));
        float v1 = (__uint_as_float(e[0]) + __uint_as_float(e[1])) + (__uint_as_float(e[2]) + __uint_as_float(e[3]));
        v0 += __shfl_xor_sync(0xffffffffu, v0, 8); v1 += __shfl_xor_sync(0xffffffffu, v1, 8);
        v0 += __shfl_xor_sync(0xffffffffu, v0, 16); v1 += __shfl_xor_sync(0xffffffffu, v1, 16);
        if (lane < 8) sts64f(sb + SM_SP + warp * 64 + lane * 8, v0, v1);
        if (warp == 0) {
            async8();
            uint32_t r[2];
            sum8(r);
            const uint32_t y0 = hadd2(x1v[0], hmul2(gbv[0], r[0])), y1 = hadd2(x1v[1], hmul2(gbv[1], r[1]));
            uint32_t* o32 = reinterpret_cast<uint32_t*>(out);
            if (lane < 8) o32[(lane >> 2) * (D_ / 2) + (rcol >> 1)] = __byte_perm(y0, y1, (lane & 4) ? 0x7632 : 0x5410);
            if (cta == 0 && lane == 0) asm volatile("st.relaxed.gpu.global.u32 [%0], %1;" ::"l"(&gs->epoch), "r"(tag) : "memory");
            TS(20);
        } else {
            asm volatile("bar.arrive 2, 256;" ::: "memory");
        }
    }
}

typedef CUresult (*EncodeFn)(CUtensorMap*, CUtensorMapDataType, cuuint32_t, void*, const cuuint64_t*, const cuuint64_t*, const cuuint32_t*,
                             const cuuint32_t*, CUtensorMapInterleave, CUtensorMapSwizzle, CUtensorMapL2promotion, CUtensorMapFloatOOBfill);

void make_map(EncodeFn fn, CUtensorMap* m, const void* p, uint64_t cols, uint64_t rows, uint32_t bcols, uint32_t brows,
              CUtensorMapSwizzle sw, CUtensorMapL2promotion pr) {
    cuuint64_t dims[2] = {cols, rows};
    cuuint64_t strides[1] = {cols * 2};
    cuuint32_t box[2] = {bcols, brows};
    cuuint32_t es[2] = {1, 1};
    fn(m, CU_TENSOR_MAP_DATA_TYPE_BFLOAT16, 2, const_cast<void*>(p), dims, strides, box, es, CU_TENSOR_MAP_INTERLEAVE_NONE, sw, pr,
       CU_TENSOR_MAP_FLOAT_OOB_FILL_NONE);
}

}

extern "C" void kernel_launch(void* const* d_in, const int* in_sizes, int n_in, void* d_out, int out_size) {
    (void)in_sizes; (void)n_in; (void)out_size;
    static EncodeFn enc = nullptr;
    if (!enc) {
        void* fp = nullptr;
        cudaDriverEntryPointQueryResult qr;
        cudaGetDriverEntryPoint("cuTensorMapEncodeTiled", &fp, cudaEnableDefault, &qr);
        enc = (EncodeFn)fp;
        cudaFuncSetAttribute(fused_block_kernel, cudaFuncAttributeMaxDynamicSharedMemorySize, SM_TOTAL);
    }
    const __nv_bfloat16* x    = (const __nv_bfloat16*)d_in[0];
    const __nv_bfloat16* wo   = (const __nv_bfloat16*)d_in[4];
    const __nv_bfloat16* w2   = (const __nv_bfloat16*)d_in[8];
    const __nv_bfloat16* cvec = (const __nv_bfloat16*)d_in[9];
    CUtensorMap tk, tv, tq, tm, t1, t3, t1x, t3x;
    make_map(enc, &tk, d_in[1], DH, 2ull * HKV * SK, 64, TILE_KEYS, CU_TENSOR_MAP_SWIZZLE_128B, CU_TENSOR_MAP_L2_PROMOTION_L2_256B);
    make_map(enc, &tv, d_in[2], DH, 2ull * HKV * SK, 64, TILE_KEYS, CU_TENSOR_MAP_SWIZZLE_128B, CU_TENSOR_MAP_L2_PROMOTION_L2_256B);
    make_map(enc, &tq, d_in[3], NQ, D_, 32, 64, CU_TENSOR_MAP_SWIZZLE_64B, CU_TENSOR_MAP_L2_PROMOTION_L2_128B);
    make_map(enc, &tm, d_in[10], NMOD, D_, 32, 64, CU_TENSOR_MAP_SWIZZLE_64B, CU_TENSOR_MAP_L2_PROMOTION_L2_128B);
    make_map(enc, &t1, d_in[6], FF, D_, 32, 64, CU_TENSOR_MAP_SWIZZLE_64B, CU_TENSOR_MAP_L2_PROMOTION_L2_128B);
    make_map(enc, &t3, d_in[7], FF, D_, 32, 64, CU_TENSOR_MAP_SWIZZLE_64B, CU_TENSOR_MAP_L2_PROMOTION_L2_128B);
    make_map(enc, &t1x, d_in[6], FF, D_, 16, 192, CU_TENSOR_MAP_SWIZZLE_32B, CU_TENSOR_MAP_L2_PROMOTION_L2_128B);
    make_map(enc, &t3x, d_in[7], FF, D_, 16, 192, CU_TENSOR_MAP_SWIZZLE_32B, CU_TENSOR_MAP_L2_PROMOTION_L2_128B);
    fused_block_kernel<<<NCTA, NTHREADS, SM_TOTAL>>>(tk, tv, tq, tm, t1, t3, t1x, t3x, x, wo, w2, cvec, (const __nv_bfloat16*)d_in[10], (__nv_bfloat16*)d_out);
}
```

```cpp
#include <cuda_runtime.h>
#include <cuda.h>
#include <cuda_bf16.h>
#include <stdint.h>

namespace {

constexpr int D_   = 576;
constexpr int HKV  = 16;
constexpr int SK   = 8192;
constexpr int DH   = 128;
constexpr int FF   = 4608;
constexpr int NQ   = 4096;
constexpr int NMOD = 6 * D_;

constexpr int NCTA     = 128;
constexpr int NCW      = 9;
constexpr int NCT      = NCW * 32;
constexpr int NTHREADS = NCT + 32;
constexpr int KEYS_PER_CTA = SK / 4;
constexpr int TILE_KEYS = 64;
constexpr int NTILES   = KEYS_PER_CTA / TILE_KEYS;
constexpr int NITEMS   = 2 * NTILES;
constexpr int TILE_BYTES = TILE_KEYS * DH * 2;
constexpr int NRING = 8;
constexpr int BOX_BYTES = 64 * 64;
constexpr int PLANE_BYTES = 9 * BOX_BYTES;
constexpr int ROWB = D_ * 2;

#define TUNE_DH 2
#define TUNE_DB 4
#define TUNE_DWO 3
#define TUNE_DW 3
#define TUNE_DW2 8
#define TUNE_M1DELAY 0
#define TUNE_DELAY 0
#define TUNE_JM2 3
#define TUNE_PRE 26

constexpr int NM1CTA = 36;
constexpr int NMODCTA = NMOD / 32;
constexpr int NWO_CTA = 96;
constexpr int NRED_CTA = 72;

constexpr int SM_RING  = 0;
constexpr int SM_X     = NRING * TILE_BYTES;
constexpr int SM_XA    = SM_X;
constexpr int SM_XB    = SM_X + PLANE_BYTES;
constexpr int SM_XW2E  = SM_X + PLANE_BYTES;
constexpr int SM_W1B8  = 186880;
constexpr int SM_W3B8  = SM_W1B8 + BOX_BYTES;
constexpr int SM_W2G7  = SM_W3B8 + BOX_BYTES + 112;
constexpr int SM_MISC  = SM_X + 2 * PLANE_BYTES;
constexpr int SM_BAR   = SM_MISC;
constexpr int SM_SP    = SM_BAR + 320;
constexpr int HSTRIDE  = 584;
constexpr int SM_SC    = SM_SP + 8192;
constexpr int SM_HB    = SM_SC + 2 * HSTRIDE * 2;
constexpr int SM_RED   = SM_HB + 2 * HSTRIDE * 2;
constexpr int SM_MB    = SM_RED + 9 * 192 * 4;
constexpr int QSTRIDE  = 136;
constexpr int SM_QS    = SM_MB + D_ * 8;
constexpr int VPSTRIDE = 56;
constexpr int SM_VP    = SM_QS + 2 * QSTRIDE * 2;
constexpr int SM_ST    = SM_VP + 2 * VPSTRIDE * 2;
constexpr int SM_FAC   = SM_ST + 9 * 16;
constexpr int SM_HIST  = SM_FAC + 16;
constexpr int SM_TOTAL = SM_HIST + 64;
static_assert(SM_TOTAL <= 232448, "smem");
static_assert(SM_W2G7 + 4 * ROWB <= SM_MISC, "smem");
static_assert(SM_X + 8 * (6 * ROWB + 16) <= SM_W1B8, "smem");
static_assert((SM_ST % 16) == 0 && (SM_RED % 16) == 0 && (SM_MB % 16) == 0 && (SM_SP % 16) == 0, "align");

enum { B_KVFULL = 0, B_KVEMPTY = 8, B_WM = 16, B_WQ = 18, B_XFREE = 20, B_FAC = 21, B_MID = 22, B_W2 = 26, B_F = 30, B_COUNT = 39 };
constexpr int SM_W1 = SM_RING, SM_W3 = SM_RING + 32768, SM_W2 = SM_RING + 65536;

typedef unsigned long long u64;
struct __align__(128) Scratch {
    u64 h1[4][D_];
    u64 mod[2][D_][2];
    u64 q[2][NQ / 2];
    u64 ml[NCTA][16];
    u64 o[NCTA][2][8][8][2];
    u64 p2[NWO_CTA][D_][2];
    u64 x1[4][NRED_CTA][16];
    u64 p4[NCTA][D_][2];
    unsigned int epoch;
};
__device__ Scratch g_s;

#define TS(i)
#define TSL(i)

__device__ __forceinline__ uint32_t smem_u32(const void* p) { return (uint32_t)__cvta_generic_to_shared(p); }
__device__ __forceinline__ float bfr(float x) { return __bfloat162float(__float2bfloat16_rn(x)); }
__device__ __forceinline__ uint32_t pack_bf(float lo, float hi) {
    uint32_t r; asm("cvt.rn.bf16x2.f32 %0, %1, %2;" : "=r"(r) : "f"(hi), "f"(lo)); return r;
}
__device__ __forceinline__ float bf_lo(uint32_t v) { return __uint_as_float(v << 16); }
__device__ __forceinline__ float bf_hi(uint32_t v) { return __uint_as_float(v & 0xffff0000u); }
__device__ __forceinline__ uint32_t hsub2(uint32_t a, uint32_t b) { uint32_t r; asm("sub.rn.bf16x2 %0, %1, %2;" : "=r"(r) : "r"(a), "r"(b)); return r; }
__device__ __forceinline__ uint32_t hadd2(uint32_t a, uint32_t b) { uint32_t r; asm("add.rn.bf16x2 %0, %1, %2;" : "=r"(r) : "r"(a), "r"(b)); return r; }
__device__ __forceinline__ uint32_t hmul2(uint32_t a, uint32_t b) { uint32_t r; asm("mul.rn.bf16x2 %0, %1, %2;" : "=r"(r) : "r"(a), "r"(b)); return r; }
__device__ __forceinline__ float ex2(float x) { float r; asm("ex2.approx.ftz.f32 %0, %1;" : "=f"(r) : "f"(x)); return r; }
__device__ __forceinline__ float rcp(float x) { float r; asm("rcp.approx.ftz.f32 %0, %1;" : "=f"(r) : "f"(x)); return r; }
constexpr float LOG2E = 1.4426950408889634f;
__device__ __forceinline__ float silu_f(float x) { return x * rcp(1.0f + ex2(-x * LOG2E)); }

__device__ __forceinline__ void mbar_init(uint32_t bar, int cnt) { asm volatile("mbarrier.init.shared::cta.b64 [%0], %1;" ::"r"(bar), "r"(cnt)); }
__device__ __forceinline__ void mbar_expect_tx(uint32_t bar, uint32_t bytes) { asm volatile("mbarrier.arrive.expect_tx.shared::cta.b64 _, [%0], %1;" ::"r"(bar), "r"(bytes) : "memory"); }
__device__ __forceinline__ void mbar_arrive(uint32_t bar) { asm volatile("mbarrier.arrive.shared::cta.b64 _, [%0];" ::"r"(bar) : "memory"); }
__device__ __forceinline__ bool mbar_try(uint32_t bar, uint32_t parity) {
    uint32_t ok;
    asm volatile("{\n.reg .pred p;\nmbarrier.try_wait.parity.shared::cta.b64 p, [%1], %2;\nselp.u32 %0, 1, 0, p;\n}\n" : "=r"(ok) : "r"(bar), "r"(parity) : "memory");
    return ok != 0;
}
__device__ __forceinline__ bool mbar_test(uint32_t bar, uint32_t parity) {
    uint32_t ok;
    asm volatile("{\n.reg .pred p;\nmbarrier.test_wait.parity.shared::cta.b64 p, [%1], %2;\nselp.u32 %0, 1, 0, p;\n}\n" : "=r"(ok) : "r"(bar), "r"(parity) : "memory");
    return ok != 0;
}
__device__ __forceinline__ void mbar_wait(uint32_t bar, uint32_t parity) {
    uint32_t spins = 0;
    while (!mbar_try(bar, parity)) { if (++spins > (1u << 22)) __trap(); }
}
__device__ __forceinline__ void bulk_g2s(uint32_t dst, const void* src, uint32_t bytes, uint32_t bar, uint64_t pol) {
    asm volatile("cp.async.bulk.shared::cluster.global.mbarrier::complete_tx::bytes.L2::cache_hint [%0], [%1], %2, [%3], %4;" ::"r"(dst), "l"(src), "r"(bytes), "r"(bar), "l"(pol) : "memory");
}
__device__ __forceinline__ void tma2d(uint32_t dst, const CUtensorMap* map, int c0, int c1, uint32_t bar, uint64_t pol) {
    asm volatile("cp.async.bulk.tensor.2d.shared::cluster.global.mbarrier::complete_tx::bytes.L2::cache_hint [%0], [%1, {%2, %3}], [%4], %5;"
                 ::"r"(dst), "l"(map), "r"(c0), "r"(c1), "r"(bar), "l"(pol) : "memory");
}
__device__ __forceinline__ void cp16(uint32_t dst, const void* src) { asm volatile("cp.async.cg.shared.global [%0], [%1], 16;" ::"r"(dst), "l"(src) : "memory"); }
__device__ __forceinline__ void cp_mbar_arrive(uint32_t bar) { asm volatile("cp.async.mbarrier.arrive.noinc.shared::cta.b64 [%0];" ::"r"(bar) : "memory"); }
__device__ __forceinline__ void csync() { asm volatile("bar.sync 1, 288;" ::: "memory"); }
__device__ __forceinline__ void async8() { asm volatile("bar.sync 2, 256;" ::: "memory"); }

__device__ __forceinline__ void ldsm4(uint32_t (&r)[4], uint32_t addr) {
    asm volatile("ldmatrix.sync.aligned.m8n8.x4.shared.b16 {%0,%1,%2,%3}, [%4];" : "=r"(r[0]), "=r"(r[1]), "=r"(r[2]), "=r"(r[3]) : "r"(addr) : "memory");
}
__device__ __forceinline__ void ldsm4t(uint32_t (&r)[4], uint32_t addr) {
    asm volatile("ldmatrix.sync.aligned.m8n8.x4.trans.shared.b16 {%0,%1,%2,%3}, [%4];" : "=r"(r[0]), "=r"(r[1]), "=r"(r[2]), "=r"(r[3]) : "r"(addr) : "memory");
}
__device__ __forceinline__ void mma16816(float (&d)[4], uint32_t a0, uint32_t a1, uint32_t a2, uint32_t a3, uint32_t b0, uint32_t b1) {
    asm("mma.sync.aligned.m16n8k16.row.col.f32.bf16.bf16.f32 {%0,%1,%2,%3}, {%4,%5,%6,%7}, {%8,%9}, {%0,%1,%2,%3};"
                 : "+f"(d[0]), "+f"(d[1]), "+f"(d[2]), "+f"(d[3]) : "r"(a0), "r"(a1), "r"(a2), "r"(a3), "r"(b0), "r"(b1));
}
__device__ __forceinline__ uint32_t ldg32(const uint32_t* p) { uint32_t v; asm volatile("ld.global.nc.u32 %0, [%1];" : "=r"(v) : "l"(p)); return v; }
__device__ __forceinline__ uint32_t lds32(uint32_t addr) { uint32_t v; asm volatile("ld.shared.u32 %0, [%1];" : "=r"(v) : "r"(addr) : "memory"); return v; }
__device__ __forceinline__ float ldsf(uint32_t addr) { float v; asm volatile("ld.shared.f32 %0, [%1];" : "=f"(v) : "r"(addr) : "memory"); return v; }
__device__ __forceinline__ uint4 lds128(uint32_t addr) { uint4 v; asm volatile("ld.shared.v4.u32 {%0,%1,%2,%3}, [%4];" : "=r"(v.x), "=r"(v.y), "=r"(v.z), "=r"(v.w) : "r"(addr) : "memory"); return v; }
__device__ __forceinline__ void sts32(uint32_t addr, uint32_t v) { asm volatile("st.shared.u32 [%0], %1;" ::"r"(addr), "r"(v) : "memory"); }
__device__ __forceinline__ void sts16(uint32_t addr, float v) { asm volatile("{\n.reg .b16 h;\ncvt.rn.bf16.f32 h, %1;\nst.shared.b16 [%0], h;\n}\n" ::"r"(addr), "f"(v) : "memory"); }
__device__ __forceinline__ void sts64(uint32_t addr, uint32_t a, uint32_t b) { asm volatile("st.shared.v2.u32 [%0], {%1,%2};" ::"r"(addr), "r"(a), "r"(b) : "memory"); }
__device__ __forceinline__ void sts64f(uint32_t addr, float a, float b) { asm volatile("st.shared.v2.f32 [%0], {%1,%2};" ::"r"(addr), "f"(a), "f"(b) : "memory"); }
__device__ __forceinline__ void sts128(uint32_t addr, uint4 v) { asm volatile("st.shared.v4.u32 [%0], {%1,%2,%3,%4};" ::"r"(addr), "r"(v.x), "r"(v.y), "r"(v.z), "r"(v.w) : "memory"); }

__device__ __forceinline__ void st_pkt(u64* p, uint32_t v, uint32_t tag) {
    asm volatile("{\n.reg .b64 t;\nmov.b64 t, {%1,%2};\nst.relaxed.gpu.global.b64 [%0], t;\n}\n" ::"l"(p), "r"(v), "r"(tag) : "memory");
}
__device__ __forceinline__ void st_pkt2(u64* p, uint32_t a, uint32_t b, uint32_t tag) {
    asm volatile("{\n.reg .b64 t,u;\nmov.b64 t, {%1,%3};\nmov.b64 u, {%2,%3};\nst.relaxed.gpu.global.v2.b64 [%0], {t,u};\n}\n" ::"l"(p), "r"(a), "r"(b), "r"(tag) : "memory");
}
template <int OFF>
__device__ __forceinline__ void st_pkt2_if(bool p, const u64* base, float a, float b, uint32_t tag) {
    asm volatile("{\n.reg .pred p;\n.reg .b64 t,u;\nsetp.ne.u32 p, %4, 0;\nmov.b64 t, {%1,%3};\nmov.b64 u, {%2,%3};\n@p st.relaxed.gpu.global.v2.b64 [%0+%5], {t,u};\n}\n"
                 ::"l"(base), "r"(__float_as_uint(a)), "r"(__float_as_uint(b)), "r"(tag), "r"((uint32_t)p), "n"(OFF) : "memory");
}
__device__ __forceinline__ uint4 ld_pkt2(const u64* p) {
    uint4 v;
    asm volatile("{\n.reg .b64 t,u;\nld.relaxed.gpu.global.v2.b64 {t,u}, [%4];\nmov.b64 {%0,%1}, t;\nmov.b64 {%2,%3}, u;\n}\n"
                 : "=r"(v.x), "=r"(v.y), "=r"(v.z), "=r"(v.w) : "l"(p) : "memory");
    return v;
}
template <int N>
__device__ __forceinline__ void pollN(const u64* p, int stride, uint32_t tag, uint32_t (&a)[N], uint32_t (&b)[N]) {
    uint32_t spins = 0;
    while (true) {
        uint4 v[N];
#pragma unroll
        for (int i = 0; i < N; i++) v[i] = ld_pkt2(p + (size_t)i * stride);
        uint32_t bad = 0;
#pragma unroll
        for (int i = 0; i < N; i++) { bad |= (v[i].y ^ tag) | (v[i].w ^ tag); a[i] = v[i].x; b[i] = v[i].z; }
        if (!__any_sync(0xffffffffu, bad != 0)) break;
        if (++spins > (1u << 22)) __trap();
    }
}

__device__ __forceinline__ void publish4(const float (&a)[4][4], int c, const u64* dst, uint32_t tag) {
    float v[4];
#pragma unroll
    for (int k = 0; k < 4; k++) {
        const float lo = (c & 1) ? a[1][k] : a[0][k], hi = (c & 1) ? a[3][k] : a[2][k];
        v[k] = (c & 2) ? hi : lo;
    }
    st_pkt2_if<0>(true, dst, v[0], v[1], tag);
    st_pkt2_if<128>(true, dst, v[2], v[3], tag);
}

__device__ __noinline__ void plane_gemv(uint32_t plane, uint32_t vec, uint32_t red, int warp, int lane) {
    const int g = lane >> 2, c = lane & 3, mi = lane >> 3, kap = lane & 7;
    const int rowl = kap + 8 * (mi >> 1);
    const uint32_t a0 = plane + warp * BOX_BYTES + rowl * 64 + ((((mi & 1)) ^ ((rowl >> 1) & 3)) << 4);
    const uint32_t bo = vec + (g & 1) * (HSTRIDE * 2) + warp * 128 + c * 4;
    float acc0[4] = {0.f, 0.f, 0.f, 0.f}, acc1[4] = {0.f, 0.f, 0.f, 0.f};
#pragma unroll
    for (int s = 0; s < 4; s++) {
        uint32_t x[4], y[4];
        ldsm4t(x, a0 + s * 1024);
        ldsm4t(y, (a0 ^ 32) + s * 1024);
        const uint32_t b0 = lds32(bo + s * 32), b1 = lds32(bo + s * 32 + 16);
        mma16816(acc0, x[0], x[1], x[2], x[3], b0, b1);
        mma16816(acc1, y[0], y[1], y[2], y[3], b0, b1);
    }
    if (c == 0) {
        const uint32_t r = red + warp * 768 + g * 8;
        sts64f(r, acc0[0], acc0[1]); sts64f(r + 64, acc0[2], acc0[3]);
        sts64f(r + 128, acc1[0], acc1[1]); sts64f(r + 192, acc1[2], acc1[3]);
    }
}
__device__ __forceinline__ float red9(uint32_t red, int idx) {
    float v[9];
#pragma unroll
    for (int w = 0; w < 9; w++) v[w] = ldsf(red + w * 768 + idx * 4);
    return ((v[0] + v[1]) + (v[2] + v[3])) + ((v[4] + v[5]) + (v[6] + v[7])) + v[8];
}

__device__ __forceinline__ void ln_stats(uint32_t xa, uint32_t xb, uint32_t sh, uint32_t st, int warp, int lane, uint32_t& mean2, float& r0, float& r1) {
    const float s0 = bf_lo(sh), s1 = bf_hi(sh);
    const float a0 = bf_lo(xa) - s0, a1 = bf_hi(xa) - s1, b0 = bf_lo(xb) - s0, b1 = bf_hi(xb) - s1;
    float u0 = a0 + b0, u1 = a1 + b1, q0 = a0 * a0 + b0 * b0, q1 = a1 * a1 + b1 * b1;
#pragma unroll
    for (int o = 16; o > 0; o >>= 1) {
        u0 += __shfl_xor_sync(0xffffffffu, u0, o); u1 += __shfl_xor_sync(0xffffffffu, u1, o);
        q0 += __shfl_xor_sync(0xffffffffu, q0, o); q1 += __shfl_xor_sync(0xffffffffu, q1, o);
    }
    if (lane == 0) sts128(st + warp * 16, make_uint4(__float_as_uint(u0), __float_as_uint(u1), __float_as_uint(q0), __float_as_uint(q1)));
    csync();
    uint4 v[9];
#pragma unroll
    for (int w = 0; w < 9; w++) v[w] = lds128(st + w * 16);
#define SUM9(f) ((((__uint_as_float(v[0].f) + __uint_as_float(v[1].f)) + (__uint_as_float(v[2].f) + __uint_as_float(v[3].f))) + \
                  ((__uint_as_float(v[4].f) + __uint_as_float(v[5].f)) + (__uint_as_float(v[6].f) + __uint_as_float(v[7].f)))) + __uint_as_float(v[8].f))
    u0 = SUM9(x) * (1.0f / D_); u1 = SUM9(y) * (1.0f / D_);
    q0 = SUM9(z); q1 = SUM9(w);
#undef SUM9
    const uint32_t var2 = pack_bf(fmaxf(fmaf(q0, 1.0f / D_, -u0 * u0), 0.f), fmaxf(fmaf(q1, 1.0f / D_, -u1 * u1), 0.f));
    mean2 = pack_bf(u0 + s0, u1 + s1);
    const uint32_t ve2 = pack_bf(bf_lo(var2) + 1e-5f, bf_hi(var2) + 1e-5f);
    float d0, d1;
    asm("sqrt.approx.ftz.f32 %0, %1;" : "=f"(d0) : "f"(bf_lo(ve2)));
    asm("sqrt.approx.ftz.f32 %0, %1;" : "=f"(d1) : "f"(bf_hi(ve2)));
    const uint32_t sd2 = pack_bf(d0, d1);
    r0 = rcp(bf_lo(sd2)); r1 = rcp(bf_hi(sd2));
}
__device__ __forceinline__ uint32_t modulate2(uint32_t x, uint32_t mean2, float r0, float r1, uint32_t shift, uint32_t onepscale) {
    const uint32_t d = hsub2(x, mean2);
    const uint32_t y = pack_bf(bf_lo(d) * r0, bf_hi(d) * r1);
    return hadd2(hmul2(y, onepscale), shift);
}
constexpr uint32_t ONE2 = 0x3f803f80u;

__global__ void __launch_bounds__(NTHREADS, 1)
fused_block_kernel(const __grid_constant__ CUtensorMap tm_k, const __grid_constant__ CUtensorMap tm_v,
                   const __grid_constant__ CUtensorMap tm_wq, const __grid_constant__ CUtensorMap tm_wm,
                   const __grid_constant__ CUtensorMap tm_w1, const __grid_constant__ CUtensorMap tm_w3,
                   const __grid_constant__ CUtensorMap tm_w1x, const __grid_constant__ CUtensorMap tm_w3x,
                   const __nv_bfloat16* __restrict__ x, const __nv_bfloat16* __restrict__ wo, const __nv_bfloat16* __restrict__ w2,
                   const __nv_bfloat16* __restrict__ cvec, const __nv_bfloat16* __restrict__ wmod, __nv_bfloat16* __restrict__ out) {
    extern __shared__ __align__(1024) uint8_t smem[];
    int tid, cta;
    uint32_t sb;
    Scratch* gs;
    asm volatile("mov.u32 %0, %1;" : "=r"(tid) : "r"(threadIdx.x));
    asm volatile("mov.u32 %0, %1;" : "=r"(cta) : "r"(blockIdx.x));
    asm volatile("mov.u32 %0, %1;" : "=r"(sb) : "r"(smem_u32(smem)));
    asm volatile("mov.u64 %0, %1;" : "=l"(gs) : "l"(&g_s));
    const int warp = tid >> 5, lane = tid & 31;
    auto BAR = [&](int i) { return sb + SM_BAR + 8 * i; };

    const int bb = cta >> 6, kvh = (cta >> 2) & 15;
    const bool typeA = cta < 32;
    const int wj = cta - 32;
    const int nO = typeA ? 0 : (wj < 32 ? 2 : 3);
    const int o_r0 = wj < 32 ? 32 * wj : 1024 + 48 * (wj - 32);
    const bool m1 = cta < NM1CTA, m2 = cta >= NM1CTA && cta < NMODCTA;

    TS(0);
    const int krow0 = cta * KEYS_PER_CTA;
    const uint32_t* x32 = reinterpret_cast<const uint32_t*>(x);
    uint64_t pol;
    asm volatile("createpolicy.fractional.L2::evict_first.b64 %0, 1.0;" : "=l"(pol));
    if (tid == NCT) {
        mbar_init(BAR(B_WQ), 1); mbar_init(BAR(B_WQ + 1), 1); mbar_init(BAR(B_KVFULL), 1);
        asm volatile("fence.mbarrier_init.release.cluster;" ::: "memory");
        TSL(22);
        mbar_expect_tx(BAR(B_WQ), 5 * BOX_BYTES);
#pragma unroll
        for (int i = 0; i < 5; i++) tma2d(sb + SM_XB + (i < 4 ? i : 8) * BOX_BYTES, &tm_wq, cta * 32, (i < 4 ? i : 8) * 64, BAR(B_WQ), pol);
        mbar_expect_tx(BAR(B_WQ + 1), 4 * BOX_BYTES);
#pragma unroll
        for (int i = 4; i < 8; i++) tma2d(sb + SM_XB + i * BOX_BYTES, &tm_wq, cta * 32, i * 64, BAR(B_WQ + 1), pol);
        mbar_expect_tx(BAR(B_KVFULL), TILE_BYTES);
        tma2d(sb + SM_RING, &tm_k, 0, krow0, BAR(B_KVFULL), pol);
        tma2d(sb + SM_RING + 8192, &tm_k, 64, krow0, BAR(B_KVFULL), pol);
#pragma unroll
        for (int i = 1; i < 8; i++) mbar_init(BAR(B_KVFULL + i), 1);
#pragma unroll
        for (int i = 0; i < 8; i++) mbar_init(BAR(B_KVEMPTY + i), 8);
        mbar_init(BAR(B_WM), 1); mbar_init(BAR(B_WM + 1), 1);
#pragma unroll
        for (int i = B_FAC; i < B_COUNT; i++) mbar_init(BAR(i), 1);
        mbar_init(BAR(B_XFREE), NCW);
        asm volatile("fence.mbarrier_init.release.cluster;" ::: "memory");
    }
    uint32_t tag, c0 = 0, c1 = 0, u0 = 0, u1 = 0, z0 = 0, z1 = 0, xo0 = 0, xo1 = 0;
    asm volatile("ld.relaxed.gpu.global.u32 %0, [%1];" : "=r"(tag) : "l"(&gs->epoch) : "memory");
    if (cta < NMODCTA && warp < NCW) {
        const uint32_t* c32 = reinterpret_cast<const uint32_t*>(cvec);
        c0 = ldg32(c32 + tid); c1 = ldg32(c32 + D_ / 2 + tid);
        if (m1) {
            u0 = ldg32(x32 + tid); u1 = ldg32(x32 + D_ / 2 + tid);
            z0 = ldg32(x32); z1 = ldg32(x32 + D_ / 2);
            xo0 = ldg32(x32 + cta * 8 + (lane >> 2)); xo1 = ldg32(x32 + D_ / 2 + cta * 8 + (lane >> 2));
            const int g = lane >> 2, c = lane & 3;
            const char* src = reinterpret_cast<const char*>(wmod) + (size_t)(warp * 64 + g) * (NMOD * 2) + (c & 1) * (D_ * 2) + cta * 32 + (c >> 1) * 16;
            const uint32_t dst = sb + SM_XA + (warp * 64 + g) * 64 + ((c ^ ((g >> 1) & 3)) << 4);
#pragma unroll
            for (int i = 0; i < 8; i++) cp16(dst + i * 512, src + (size_t)i * 8 * (NMOD * 2));
        }
    }
    if (warp == NCW) {
        __syncwarp();
        asm volatile("bar.arrive 0, 320;" ::: "memory");
        if (lane != 0) return;
        const uint32_t hist = sb + SM_HIST;
        sts32(hist, BAR(B_WQ)); sts32(hist + 4, BAR(B_WQ + 1)); sts32(hist + 8, BAR(B_KVFULL));
        int n = 3;
        auto window = [&](int D) {
            if (n >= D) { const uint32_t h = lds32(hist + ((n - D) & 15) * 4); mbar_wait(h & ~1u, h & 1u); }
        };
        auto issued = [&](uint32_t bar, uint32_t par) { sts32(hist + (n & 15) * 4, bar | par); n++; };
        auto plane_half = [&](const CUtensorMap* map, uint32_t base, uint32_t box8, int bar, int half, int D) {
            window(D);
            mbar_expect_tx(BAR(bar + half), (half ? 4 : 5) * BOX_BYTES);
#pragma unroll
            for (int i = 0; i < 4; i++) tma2d(base + (half * 4 + i) * BOX_BYTES, map, cta * 32, (half * 4 + i) * 64, BAR(bar + half), pol);
            if (!half) tma2d(box8, map, cta * 32, 512, BAR(bar), pol);
            issued(BAR(bar + half), 0);
        };
        auto rows8 = [&](const __nv_bfloat16* w, int row0, int rpg, uint32_t base, uint32_t g7, uint32_t bar, int g0, int ng) {
            const uint32_t gb = rpg * ROWB;
#pragma unroll 1
            for (int gi = g0; gi < g0 + ng; gi++)
                bulk_g2s(gi < 7 ? base + gi * (gb + 16) : g7, reinterpret_cast<const char*>(w) + (size_t)row0 * ROWB + (size_t)gi * gb, gb, bar, pol);
        };
#pragma unroll 1
        for (int j = 1; j < NITEMS; j++) {
            const int s = j & 7;
            int D = TUNE_DB;
            if (j >= 8) mbar_wait(BAR(B_KVEMPTY + s), ((j >> 3) - 1) & 1);
            else if (!mbar_test(BAR(B_KVEMPTY), 0)) D = TUNE_DH;
            window(D);
            if (j == 4) TSL(90); if (j == 7) TSL(91); if (j == 8) TSL(92); if (j == 12) TSL(93);
            mbar_expect_tx(BAR(B_KVFULL + s), TILE_BYTES);
            const CUtensorMap* map = j < NTILES ? &tm_k : &tm_v;
            tma2d(sb + SM_RING + s * TILE_BYTES, map, 0, krow0 + (j & 31) * TILE_KEYS, BAR(B_KVFULL + s), pol);
            tma2d(sb + SM_RING + s * TILE_BYTES + 8192, map, 64, krow0 + (j & 31) * TILE_KEYS, BAR(B_KVFULL + s), pol);
            issued(BAR(B_KVFULL + s), (j >> 3) & 1);
            if (m2 && (j == TUNE_JM2 || j == TUNE_JM2 + 1)) plane_half(&tm_wm, sb + SM_XA, sb + SM_XA + 8 * BOX_BYTES, B_WM, j - TUNE_JM2, D);
        }
        TSL(16);
        mbar_wait(BAR(B_XFREE), 0);
        if (!typeA) {
#pragma unroll 1
            for (int h = 0; h < 4; h++) {
                window(TUNE_DWO);
                mbar_expect_tx(BAR(B_MID + h), 4 * nO * ROWB);
                rows8(wo, o_r0, 2 * nO, sb + SM_X, sb + SM_X + 7 * (2 * nO * ROWB + 16), BAR(B_MID + h), 2 * h, 2);
                issued(BAR(B_MID + h), 0);
            }
        }
        bool open = false;
        uint32_t spins = 0;
        auto tail_window = [&]() {
            while (!open) {
                const uint32_t h = lds32(hist + ((n - TUNE_DW) & 15) * 4);
                if (mbar_test(h & ~1u, h & 1u)) return;
                const uint4 v = ld_pkt2(&gs->x1[cta & 3][(cta * 5) % NRED_CTA][0]);
                open = v.y == tag + 1;
                if (++spins > (1u << 22)) __trap();
            }
            window(TUNE_DW2);
        };
#pragma unroll 1
        for (int i = 0; i < 9; i++) {
            const int bx = i == 0 ? 8 : i - 1;
            if (i == 1) { mbar_wait(BAR(B_KVEMPTY + 0), 1); mbar_wait(BAR(B_KVEMPTY + 2), 1); }
            if (i == 5) { mbar_wait(BAR(B_KVEMPTY + 1), 1); mbar_wait(BAR(B_KVEMPTY + 3), 1); }
            tail_window();
            mbar_expect_tx(BAR(B_F + bx), 2 * BOX_BYTES);
            tma2d(sb + (i ? SM_W1 + bx * BOX_BYTES : SM_W1B8), &tm_w1, cta * 32, bx * 64, BAR(B_F + bx), pol);
            tma2d(sb + (i ? SM_W3 + bx * BOX_BYTES : SM_W3B8), &tm_w3, cta * 32, bx * 64, BAR(B_F + bx), pol);
            issued(BAR(B_F + bx), 0);
            if (typeA && i < 4) {
                tail_window();
                mbar_expect_tx(BAR(B_MID + i), i < 3 ? 2 * 6144 : 16 * ROWB);
                if (i < 3) {
                    tma2d(sb + SM_XA + i * 6144, &tm_w1x, NQ + 16 * cta, i * 192, BAR(B_MID + i), pol);
                    tma2d(sb + SM_XA + 18432 + i * 6144, &tm_w3x, NQ + 16 * cta, i * 192, BAR(B_MID + i), pol);
                } else rows8(w2, NQ + 16 * cta, 2, sb + SM_XW2E, sb + SM_XW2E + 7 * (2 * ROWB + 16), BAR(B_MID + 3), 0, 8);
                issued(BAR(B_MID + i), 0);
            }
        }
        mbar_wait(BAR(B_KVEMPTY + 4), 1);
        mbar_wait(BAR(B_KVEMPTY + 5), 1);
#pragma unroll 1
        for (int h = 0; h < 4; h++) {
            tail_window();
            mbar_expect_tx(BAR(B_W2 + h), 8 * ROWB);
            rows8(w2, cta * 32, 4, sb + SM_W2, sb + SM_W2G7, BAR(B_W2 + h), 2 * h, 2);
            issued(BAR(B_W2 + h), 0);
        }
        TSL(17);
        return;
    }

    const int g = lane >> 2, c = lane & 3, mi = lane >> 3, kap = lane & 7;
    const int whalf = (warp >> 2) & 1;
    const int rowl = kap + 8 * (mi >> 1);
    const uint32_t sw64 = (rowl >> 1) & 3;
    const uint32_t hbo = sb + SM_HB + (g & 1) * (HSTRIDE * 2) + warp * 128 + c * 4;
    const uint32_t redw = sb + SM_RED + warp * 768 + g * 8;
    if (cta < NMODCTA) {
        sts32(sb + SM_SC + tid * 4, pack_bf(silu_f(bf_lo(c0)), silu_f(bf_hi(c0))));
        sts32(sb + SM_SC + HSTRIDE * 2 + tid * 4, pack_bf(silu_f(bf_lo(c1)), silu_f(bf_hi(c1))));
        if (m1) {
            uint32_t mean2; float r0, r1;
            ln_stats(__byte_perm(u0, u1, 0x5410), __byte_perm(u0, u1, 0x7632), __byte_perm(z0, z1, 0x5410), sb + SM_ST, warp, lane, mean2, r0, r1);
            asm volatile("cp.async.wait_all;" ::: "memory");
            __syncwarp();
            TSL(70 + warp);
            plane_gemv(sb + SM_XA, sb + SM_SC, sb + SM_RED, warp, lane);
            csync();
            if (warp == 0) {
                const int idx = (lane >> 4) * 32 + (lane & 15);
                const float sa = red9(sb + SM_RED, idx), ca = red9(sb + SM_RED, idx + 16);
                const uint32_t sa2 = pack_bf(sa, __shfl_xor_sync(0xffffffffu, sa, 1)), ca2 = pack_bf(ca, __shfl_xor_sync(0xffffffffu, ca, 1));
                const uint32_t xo = __byte_perm(xo0, xo1, (lane & 2) ? 0x7632 : 0x5410);
                const uint32_t h = modulate2(xo, mean2, r0, r1, sa2, hadd2(ca2, ONE2));
                const uint32_t hp = __shfl_sync(0xffffffffu, h, (lane & 7) * 4), hq = __shfl_sync(0xffffffffu, h, (lane & 7) * 4 + 2);
                st_pkt2(&gs->h1[lane >> 3][cta * 16 + (lane & 7) * 2], hp, hq, tag + 1);
            }
            TS(2);
        }
    }
    tag += 1;
    asm volatile("bar.sync 0, 320;" ::: "memory");
    TS(1);
    {
        uint32_t af[4][2][4];
        const uint32_t a0 = sb + SM_XB + warp * BOX_BYTES + rowl * 64 + (((mi & 1) ^ sw64) << 4);
        mbar_wait(BAR(B_WQ + whalf), 0);
        TS(21);
#pragma unroll
        for (int s = 0; s < 4; s++) { ldsm4t(af[s][0], a0 + s * 1024); ldsm4t(af[s][1], (a0 ^ 32) + s * 1024); }
        uint32_t ha[1], hb[1];
        pollN<1>(&gs->h1[cta & 3][2 * tid], 0, tag, ha, hb);
        sts32(sb + SM_HB + tid * 4, __byte_perm(ha[0], hb[0], 0x5410));
        sts32(sb + SM_HB + HSTRIDE * 2 + tid * 4, __byte_perm(ha[0], hb[0], 0x7632));
        __syncwarp();
        TS(3);
        float acc0[4] = {0.f, 0.f, 0.f, 0.f}, acc1[4] = {0.f, 0.f, 0.f, 0.f};
#pragma unroll
        for (int s = 0; s < 4; s++) {
            const uint32_t b0 = lds32(hbo + s * 32), b1 = lds32(hbo + s * 32 + 16);
            mma16816(acc0, af[s][0][0], af[s][0][1], af[s][0][2], af[s][0][3], b0, b1);
            mma16816(acc1, af[s][1][0], af[s][1][1], af[s][1][2], af[s][1][3], b0, b1);
        }
        if (c == 0) {
            sts64f(redw, acc0[0], acc0[1]); sts64f(redw + 64, acc0[2], acc0[3]);
            sts64f(redw + 128, acc1[0], acc1[1]); sts64f(redw + 192, acc1[2], acc1[3]);
        }
        csync();
        if (warp == 0) {
            const int idx = (lane & 15) * 4 + (lane >> 4);
            st_pkt(&gs->q[lane >> 4][cta * 16 + (lane & 15)], pack_bf(red9(sb + SM_RED, idx), red9(sb + SM_RED, idx + 2)), tag);
        }
    }
    TS(4);
    auto mod2_phase = [&]() {
        if (m2) {
            mbar_wait(BAR(B_WM + whalf), 0);
            plane_gemv(sb + SM_XA, sb + SM_SC, sb + SM_RED, warp, lane);
            csync();
            if (tid < 64) {
                const float v = red9(sb + SM_RED, tid);
                const float o = __shfl_xor_sync(0xffffffffu, v, 1);
                const int which = cta / 18, i = (cta % 18) * 32 + (tid >> 1);
                if ((tid & 1) == 0) st_pkt(&gs->mod[(which == 2 || which == 5) ? 1 : 0][i][which >> 2], pack_bf(v, o), tag);
            }
        }
        asm volatile("fence.proxy.async.shared::cta;" ::: "memory");
        __syncwarp();
        if (lane == 0) mbar_arrive(BAR(B_XFREE));
    };

    const bool reducer = cta < NRED_CTA;
    const int rcol = cta * 8 + (lane & 3) * 2;
    uint32_t gav[2] = {0, 0}, gbv[2] = {0, 0}, xin[2] = {0, 0};
    auto preload_tail = [&]() {
        if (reducer && warp == 0) {
            const uint32_t u0 = __ldg(x32 + (rcol >> 1)), u1 = __ldg(x32 + ((D_ + rcol) >> 1));
            xin[0] = __byte_perm(u0, u1, 0x5410); xin[1] = __byte_perm(u0, u1, 0x7632);
            pollN<2>(&gs->mod[1][rcol][0], 2, tag, gav, gbv);
        }
    };

    if (warp == 8) {
#pragma unroll 2
        for (int i = lane; i < D_; i += 32) {
            st_pkt2(&gs->p4[cta][i][0], 0u, 0u, 0u);
            if (!typeA) st_pkt2(&gs->p2[wj][i][0], 0u, 0u, 0u);
            if (i < DH) st_pkt2(&gs->o[cta][0][0][0][0] + 2 * i, 0u, 0u, 0u);
        }
        asm volatile("bar.sync 3, 64;" ::: "memory");
        mod2_phase();
#pragma unroll 1
        for (int i = lane; i < D_; i += 64) {
            uint32_t s2[2], c2[2];
            pollN<2>(&gs->mod[0][i][0], 64, tag, s2, c2);
            sts64(sb + SM_MB + i * 8, s2[0], hadd2(c2[0], ONE2));
            sts64(sb + SM_MB + (i + 32) * 8, s2[1], hadd2(c2[1], ONE2));
        }
        {
            uint32_t a[1], e[1];
            pollN<1>(&gs->ml[(cta & ~3) + ((lane >> 1) & 3)][(lane & 1) * 2], 0, tag, a, e);
            const float m = __uint_as_float(a[0]);
            float M = fmaxf(m, __shfl_xor_sync(0xffffffffu, m, 2));
            M = fmaxf(M, __shfl_xor_sync(0xffffffffu, M, 4));
            const float w = ex2((m - M) * LOG2E);
            float L = w * __uint_as_float(e[0]);
            L += __shfl_xor_sync(0xffffffffu, L, 2);
            L += __shfl_xor_sync(0xffffffffu, L, 4);
            if ((lane >> 1) == (cta & 3)) sts32(sb + SM_FAC + (lane & 1) * 4, __float_as_uint(w / L));
        }
        __syncwarp();
        if (lane == 0) mbar_arrive(BAR(B_FAC));
        preload_tail();
    } else {
        if (tid < 64) {
            uint32_t a[1], e[1];
            pollN<1>(&gs->q[bb][kvh * 128 + tid * 2], 0, tag, a, e);
            sts64(sb + SM_QS + (tid >> 5) * (QSTRIDE * 2) + (tid & 31) * 8, a[0], e[0]);
        }
        async8();
        if (warp == 7) asm volatile("bar.arrive 3, 64;" ::: "memory");
        TS(5);
        uint32_t qa[8][2];
#pragma unroll
        for (int s = 0; s < 8; s++) {
            const uint32_t a = sb + SM_QS + (g & 1) * (QSTRIDE * 2) + (16 * s + 2 * c) * 2;
            qa[s][0] = lds32(a); qa[s][1] = lds32(a + 16);
        }
        constexpr float SCALE = 0.08838834764831845f;
        float mrun = -INFINITY;
        const uint32_t koff = (8 * warp + kap) * 128 + ((mi ^ kap) << 4);
        const uint32_t spw = sb + SM_SP + (g & 1) * 128 + c * 32;
#pragma unroll 1
        for (int t = 0; t < NTILES; t++) {
            const int s = t & 7;
            mbar_wait(BAR(B_KVFULL + s), (t >> 3) & 1);
            if ((t & 3) == 0) TS(24 + (t >> 2));
            float s0[4] = {0.f, 0.f, 0.f, 0.f}, s1[4] = {0.f, 0.f, 0.f, 0.f};
            const uint32_t ka = sb + SM_RING + s * TILE_BYTES + koff;
#pragma unroll
            for (int i = 0; i < 4; i++) {
                uint32_t u[4];
                ldsm4(u, (ka ^ ((i & 1) << 6)) + (i >> 1) * 8192);
                mma16816(s0, qa[2 * i][0], 0u, qa[2 * i][1], 0u, u[0], u[1]);
                mma16816(s1, qa[2 * i + 1][0], 0u, qa[2 * i + 1][1], 0u, u[2], u[3]);
            }
            __syncwarp();
            if (lane == 0) mbar_arrive(BAR(B_KVEMPTY + s));
            const uint32_t d0 = pack_bf(s0[0] + s1[0], s0[1] + s1[1]);
            const uint32_t e0 = pack_bf(bf_lo(d0) * SCALE, bf_hi(d0) * SCALE);
            mrun = fmaxf(mrun, fmaxf(bf_lo(e0), bf_hi(e0)));
            if (g < 2) sts32(spw + t * 256 + warp * 4, e0);
        }
        TS(6);
        mrun = fmaxf(mrun, __shfl_xor_sync(0xffffffffu, mrun, 1));
        mrun = fmaxf(mrun, __shfl_xor_sync(0xffffffffu, mrun, 2));
        if (lane == 0 || lane == 4) sts32(sb + SM_ST + (g * 8 + warp) * 4, __float_as_uint(mrun));
        async8();
        {
            const int h = (tid >> 2) & 1;
            const uint4 m0 = lds128(sb + SM_ST + h * 32), m1v = lds128(sb + SM_ST + h * 32 + 16);
            const float M = fmaxf(fmaxf(fmaxf(__uint_as_float(m0.x), __uint_as_float(m0.y)), fmaxf(__uint_as_float(m0.z), __uint_as_float(m0.w))),
                                  fmaxf(fmaxf(__uint_as_float(m1v.x), __uint_as_float(m1v.y)), fmaxf(__uint_as_float(m1v.z), __uint_as_float(m1v.w))));
            const float Ms = M * LOG2E;
            float l = 0.f;
#pragma unroll
            for (int k = 0; k < 2; k++) {
                uint4 v = lds128(sb + SM_SP + tid * 32 + k * 16);
                uint32_t* w = reinterpret_cast<uint32_t*>(&v);
#pragma unroll
                for (int i = 0; i < 4; i++) {
                    const float p0 = ex2(fmaf(bf_lo(w[i]), LOG2E, -Ms)), p1 = ex2(fmaf(bf_hi(w[i]), LOG2E, -Ms));
                    l += p0 + p1;
                    w[i] = pack_bf(p0, p1);
                }
                sts128(sb + SM_SP + tid * 32 + k * 16, v);
            }
            l += __shfl_xor_sync(0xffffffffu, l, 1); l += __shfl_xor_sync(0xffffffffu, l, 2);
            l += __shfl_xor_sync(0xffffffffu, l, 8); l += __shfl_xor_sync(0xffffffffu, l, 16);
            if (lane == 0 || lane == 4) sts32(sb + SM_ST + 64 + (h * 8 + warp) * 4, __float_as_uint(l));
            async8();
            if (tid == 0 || tid == 4) {
                const uint4 l0 = lds128(sb + SM_ST + 64 + h * 32), l1 = lds128(sb + SM_ST + 64 + h * 32 + 16);
                const float L = ((__uint_as_float(l0.x) + __uint_as_float(l0.y)) + (__uint_as_float(l0.z) + __uint_as_float(l0.w))) +
                                ((__uint_as_float(l1.x) + __uint_as_float(l1.y)) + (__uint_as_float(l1.z) + __uint_as_float(l1.w)));
                st_pkt2(&gs->ml[cta][h * 2], __float_as_uint(M), __float_as_uint(L), tag);
            }
            __syncwarp();
        }
        mod2_phase();
        TS(7);
        float oacc0[4] = {0.f, 0.f, 0.f, 0.f}, oacc1[4] = {0.f, 0.f, 0.f, 0.f};
        float f0 = 0.f, f1 = 0.f;
        const uint32_t voff = (warp >> 2) * 8192 + rowl * 128 + (((2 * (warp & 3) + (mi & 1)) ^ kap) << 4);
        const u64* odst = &gs->o[cta][c & 1][warp][g][0];
#pragma unroll 1
        for (int t = 0; t < NTILES; t++) {
            const int s = t & 7;
            uint4 pb[2];
            pb[0] = lds128(spw + t * 256); pb[1] = lds128(spw + t * 256 + 16);
            mbar_wait(BAR(B_KVFULL + s), (t >> 3) & 1);
            if ((t & 3) == 3) TS(32 + (t >> 2));
            const uint32_t va = sb + SM_RING + s * TILE_BYTES + voff;
#pragma unroll
            for (int i = 0; i < 2; i++) {
                uint32_t u[4], v[4];
                ldsm4t(u, va + (2 * i) * 2048);
                ldsm4t(v, va + (2 * i + 1) * 2048);
                mma16816(oacc0, u[0], u[1], u[2], u[3], pb[i].x, pb[i].y);
                mma16816(oacc1, v[0], v[1], v[2], v[3], pb[i].z, pb[i].w);
            }
            __syncwarp();
            if (lane == 0) mbar_arrive(BAR(B_KVEMPTY + s));
            if (t == TUNE_PRE) {
                preload_tail();
                mbar_wait(BAR(B_FAC), 0);
                f0 = ldsf(sb + SM_FAC); f1 = ldsf(sb + SM_FAC + 4);
            }
        }
        TS(8);
        {
            const float f = (c & 1) ? f1 : f0;
            const float u = (c & 1) ? oacc0[1] + oacc1[1] : oacc0[0] + oacc1[0], v = (c & 1) ? oacc0[3] + oacc1[3] : oacc0[2] + oacc1[2];
            st_pkt2_if<0>(c < 2, odst, u * f, v * f, tag);
        }
    }
    TS(9);
    const uint32_t vpb = sb + SM_VP + (g & 1) * (VPSTRIDE * 2) + c * 4;
    if (nO > 0) {
        const int j = lane & 7, s = (lane >> 3) & 3, b = warp & 1, u = warp >> 1;
        const u64* dst = &gs->p2[wj][warp * 64 + c * 16 + g][0];
        if (u < nO) {
            const int row = o_r0 + 16 * u;
            const int hq = row >> 7;
            const int r = 16 * u + j + 8 * (s & 1);
            const int grp = nO == 3 ? (r * 43) >> 8 : r >> 2, rr = r - grp * 2 * nO;
            const uint32_t vd = sb + SM_VP + b * (VPSTRIDE * 2) + (16 * (rr >> 1) + (rr & 1) * 8 + grp) * 2;
            uint32_t a[1], e[1];
            pollN<1>(&gs->o[b * 64 + (hq >> 1) * 4 + s][hq & 1][(row >> 4) & 7][j][0], 0, tag, a, e);
            float o0 = __uint_as_float(a[0]), o1 = __uint_as_float(e[0]);
            o0 += __shfl_xor_sync(0xffffffffu, o0, 8); o1 += __shfl_xor_sync(0xffffffffu, o1, 8);
            o0 += __shfl_xor_sync(0xffffffffu, o0, 16); o1 += __shfl_xor_sync(0xffffffffu, o1, 16);
            const uint32_t pk = pack_bf(o0, o1);
            if (s < 2) asm volatile("st.shared.b16 [%0], %1;" ::"r"(vd), "h"((unsigned short)(s ? pk >> 16 : pk)) : "memory");
        }
        uint32_t wof[4][3][4];
        {
            const uint32_t ab = sb + SM_X + kap * (2 * nO * ROWB + 16) + (mi >> 1) * ROWB + (mi & 1) * 16 + warp * 128;
#pragma unroll
            for (int i = 0; i < 4; i++) mbar_wait(BAR(B_MID + i), 0);
#pragma unroll
            for (int i = 0; i < 4; i++) {
                ldsm4t(wof[i][0], ab + i * 32);
                ldsm4t(wof[i][1], ab + i * 32 + 2 * ROWB);
                ldsm4t(wof[i][2], ab + i * 32 + 4 * ROWB);
            }
        }
        csync();
        TS(10);
        uint32_t b0[3], b1[3];
#pragma unroll
        for (int k = 0; k < 3; k++) { b0[k] = lds32(vpb + k * 32); b1[k] = lds32(vpb + k * 32 + 16); }
        float acc[4][4];
#pragma unroll
        for (int i = 0; i < 4; i++) { acc[i][0] = acc[i][1] = acc[i][2] = acc[i][3] = 0.f; mma16816(acc[i], wof[i][0][0], wof[i][0][1], wof[i][0][2], wof[i][0][3], b0[0], b1[0]); }
#pragma unroll
        for (int i = 0; i < 4; i++) mma16816(acc[i], wof[i][1][0], wof[i][1][1], wof[i][1][2], wof[i][1][3], b0[1], b1[1]);
        if (nO == 3) {
#pragma unroll
            for (int i = 0; i < 4; i++) mma16816(acc[i], wof[i][2][0], wof[i][2][1], wof[i][2][2], wof[i][2][3], b0[2], b1[2]);
        }
        publish4(acc, c, dst, tag);
        TSL(80 + warp);
    }
    TS(11);
    uint32_t x1v[2] = {0, 0};
    auto sum8 = [&](uint32_t (&r)[2]) {
        float v[4] = {0.f, 0.f, 0.f, 0.f}, w[4] = {0.f, 0.f, 0.f, 0.f};
#pragma unroll
        for (int k = 0; k < 8; k += 2) {
            const uint4 a = lds128(sb + SM_SP + k * 64 + (lane & 3) * 16), e = lds128(sb + SM_SP + k * 64 + 64 + (lane & 3) * 16);
            v[0] += __uint_as_float(a.x); v[1] += __uint_as_float(a.y); v[2] += __uint_as_float(a.z); v[3] += __uint_as_float(a.w);
            w[0] += __uint_as_float(e.x); w[1] += __uint_as_float(e.y); w[2] += __uint_as_float(e.z); w[3] += __uint_as_float(e.w);
        }
        r[0] = pack_bf(v[0] + w[0], v[1] + w[1]); r[1] = pack_bf(v[2] + w[2], v[3] + w[3]);
    };
    if (reducer && warp < 8) {
        uint32_t a[3], e[3];
        pollN<3>(&gs->p2[warp * 12 + (lane >> 3)][cta * 8 + (lane & 7)][0], 4 * D_ * 2, tag, a, e);
        float v0 = (__uint_as_float(a[0]) + __uint_as_float(a[1])) + __uint_as_float(a[2]);
        float v1 = (__uint_as_float(e[0]) + __uint_as_float(e[1])) + __uint_as_float(e[2]);
        v0 += __shfl_xor_sync(0xffffffffu, v0, 8); v1 += __shfl_xor_sync(0xffffffffu, v1, 8);
        v0 += __shfl_xor_sync(0xffffffffu, v0, 16); v1 += __shfl_xor_sync(0xffffffffu, v1, 16);
        if (lane < 8) sts64f(sb + SM_SP + warp * 64 + lane * 8, v0, v1);
        if (warp == 0) {
            TS(12);
            async8();
            TS(13);
            uint32_t r[2];
            sum8(r);
            x1v[0] = hadd2(xin[0], hmul2(gav[0], r[0])); x1v[1] = hadd2(xin[1], hmul2(gav[1], r[1]));
            if (lane < 16) st_pkt2(&gs->x1[lane >> 2][cta][(lane & 3) * 2], x1v[0], x1v[1], tag);
            __syncwarp();
        } else {
            asm volatile("bar.arrive 2, 256;" ::: "memory");
        }
    }
    TSL(60 + warp);
    {
        const uint32_t pb = ((mi & 1) ? (warp < 8 ? sb + SM_W3 + warp * BOX_BYTES : sb + SM_W3B8)
                                      : (warp < 8 ? sb + SM_W1 + warp * BOX_BYTES : sb + SM_W1B8)) + rowl * 64 + (sw64 << 4);
        const uint32_t pe = sb + SM_XA + (mi & 1) * 18432 + (warp * 64 + rowl) * 32 + (((rowl >> 2) & 1) << 4);
        const uint32_t ab = (kap < 7 ? sb + SM_W2 + kap * (4 * ROWB + 16) : sb + SM_W2G7) + (mi >> 1) * ROWB + (mi & 1) * 16 + warp * 128;
        const uint32_t aeb = sb + SM_XW2E + kap * (2 * ROWB + 16) + (mi >> 1) * ROWB + (mi & 1) * 16 + warp * 128;
        const u64* dst = &gs->p4[cta][warp * 64 + c * 16 + g][0];
        const int ar = tid >> 1;
        const uint32_t ared = sb + SM_RED + ((ar >> 3) * 32 + (ar & 7) * 2 + (tid & 1)) * 4;
        const uint32_t avp = sb + SM_VP + (tid & 1) * (VPSTRIDE * 2) +
                             (ar < 32 ? 16 * ((ar & 3) >> 1) + (ar & 1) * 8 + (ar >> 2) : 32 + (ar & 1) * 8 + ((ar - 32) >> 1)) * 2;
        uint32_t af[4][4][4], ae[4][2][4], wf[4][3][4];
        if (typeA) {
#pragma unroll
            for (int i = 0; i < 4; i++) mbar_wait(BAR(B_MID + i), 0);
#pragma unroll
            for (int s = 0; s < 4; s++) { ldsm4t(ae[s][0], pe + s * 512); ldsm4t(ae[s][1], (pe ^ 16) + s * 512); ldsm4t(wf[s][2], aeb + s * 32); }
        }
        const uint4 mb = lds128(sb + SM_MB + tid * 16);
        mbar_wait(BAR(B_F + warp), 0);
#pragma unroll
        for (int s = 0; s < 4; s++)
#pragma unroll
            for (int j = 0; j < 4; j++) ldsm4t(af[s][j], (pb ^ (j << 4)) + s * 1024);
        TSL(40 + warp);
        uint32_t a[2], e[2];
        pollN<2>(&gs->x1[cta & 3][tid >> 2][(tid & 3) * 2], -((tid >> 2) * 16 + (tid & 3) * 2), tag, a, e);
        TSL(50 + warp);
        uint32_t mean2; float r0, r1;
        ln_stats(a[0], e[0], a[1], sb + SM_ST, warp, lane, mean2, r0, r1);
        const uint32_t ha = modulate2(a[0], mean2, r0, r1, mb.x, mb.y);
        const uint32_t hb = modulate2(e[0], mean2, r0, r1, mb.z, mb.w);
        sts32(sb + SM_HB + tid * 4, __byte_perm(ha, hb, 0x5410));
        sts32(sb + SM_HB + HSTRIDE * 2 + tid * 4, __byte_perm(ha, hb, 0x7632));
        __syncwarp();
        float acc[6][4];
#pragma unroll
        for (int j = 0; j < 6; j++) acc[j][0] = acc[j][1] = acc[j][2] = acc[j][3] = 0.f;
#pragma unroll
        for (int s = 0; s < 4; s++) {
            const uint32_t b0 = lds32(hbo + s * 32), b1 = lds32(hbo + s * 32 + 16);
#pragma unroll
            for (int j = 0; j < 4; j++) mma16816(acc[j], af[s][j][0], af[s][j][1], af[s][j][2], af[s][j][3], b0, b1);
            if (typeA) {
                mma16816(acc[4], ae[s][0][0], ae[s][0][1], ae[s][0][2], ae[s][0][3], b0, b1);
                mma16816(acc[5], ae[s][1][0], ae[s][1][1], ae[s][1][2], ae[s][1][3], b0, b1);
            }
        }
        if (c == 0) {
#pragma unroll
            for (int j = 0; j < 6; j++) { sts64f(redw + j * 128, acc[j][0], acc[j][1]); sts64f(redw + j * 128 + 64, acc[j][2], acc[j][3]); }
        }
        TS(15);
        csync();
        if (tid < (typeA ? 96 : 64)) {
            const uint32_t gu = pack_bf(red9(ared, 0), red9(ared, 16));
            const uint32_t sg = pack_bf(silu_f(bf_lo(gu)), 0.f);
            const uint32_t hh = hmul2(sg, gu >> 16);
            asm volatile("st.shared.b16 [%0], %1;" ::"r"(avp), "h"((unsigned short)hh) : "memory");
        }
#pragma unroll
        for (int i = 0; i < 4; i++) mbar_wait(BAR(B_W2 + i), 0);
#pragma unroll
        for (int i = 0; i < 4; i++) { ldsm4t(wf[i][0], ab + i * 32); ldsm4t(wf[i][1], ab + i * 32 + 2 * ROWB); }
        csync();
        TS(18);
        uint32_t b0[3], b1[3];
#pragma unroll
        for (int k = 0; k < 3; k++) { b0[k] = lds32(vpb + k * 32); b1[k] = lds32(vpb + k * 32 + 16); }
        float o[4][4];
#pragma unroll
        for (int i = 0; i < 4; i++) { o[i][0] = o[i][1] = o[i][2] = o[i][3] = 0.f; mma16816(o[i], wf[i][0][0], wf[i][0][1], wf[i][0][2], wf[i][0][3], b0[0], b1[0]); }
#pragma unroll
        for (int i = 0; i < 4; i++) mma16816(o[i], wf[i][1][0], wf[i][1][1], wf[i][1][2], wf[i][1][3], b0[1], b1[1]);
        if (typeA) {
#pragma unroll
            for (int i = 0; i < 4; i++) mma16816(o[i], wf[i][2][0], wf[i][2][1], wf[i][2][2], wf[i][2][3], b0[2], b1[2]);
        }
        publish4(o, c, dst, tag);
    }
    TS(19);
    if (reducer && warp < 8) {
        uint32_t a[4], e[4];
        pollN<4>(&gs->p4[warp * 16 + (lane >> 3)][cta * 8 + (lane & 7)][0], 4 * D_ * 2, tag, a, e);
        float v0 = (__uint_as_float(a[0]) + __uint_as_float(a[1])) + (__uint_as_float(a[2]) + __uint_as_float(a[3]));
        float v1 = (__uint_as_float(e[0]) + __uint_as_float(e[1])) + (__uint_as_float(e[2]) + __uint_as_float(e[3]));
        v0 += __shfl_xor_sync(0xffffffffu, v0, 8); v1 += __shfl_xor_sync(0xffffffffu, v1, 8);
        v0 += __shfl_xor_sync(0xffffffffu, v0, 16); v1 += __shfl_xor_sync(0xffffffffu, v1, 16);
        if (lane < 8) sts64f(sb + SM_SP + warp * 64 + lane * 8, v0, v1);
        if (warp == 0) {
            async8();
            uint32_t r[2];
            sum8(r);
            const uint32_t y0 = hadd2(x1v[0], hmul2(gbv[0], r[0])), y1 = hadd2(x1v[1], hmul2(gbv[1], r[1]));
            uint32_t* o32 = reinterpret_cast<uint32_t*>(out);
            if (lane < 8) o32[(lane >> 2) * (D_ / 2) + (rcol >> 1)] = __byte_perm(y0, y1, (lane & 4) ? 0x7632 : 0x5410);
            if (cta == 0 && lane == 0) asm volatile("st.relaxed.gpu.global.u32 [%0], %1;" ::"l"(&gs->epoch), "r"(tag) : "memory");
            TS(20);
        } else {
            asm volatile("bar.arrive 2, 256;" ::: "memory");
        }
    }
}

typedef CUresult (*EncodeFn)(CUtensorMap*, CUtensorMapDataType, cuuint32_t, void*, const cuuint64_t*, const cuuint64_t*, const cuuint32_t*,
                             const cuuint32_t*, CUtensorMapInterleave, CUtensorMapSwizzle, CUtensorMapL2promotion, CUtensorMapFloatOOBfill);

void make_map(EncodeFn fn, CUtensorMap* m, const void* p, uint64_t cols, uint64_t rows, uint32_t bcols, uint32_t brows,
              CUtensorMapSwizzle sw, CUtensorMapL2promotion pr) {
    cuuint64_t dims[2] = {cols, rows};
    cuuint64_t strides[1] = {cols * 2};
    cuuint32_t box[2] = {bcols, brows};
    cuuint32_t es[2] = {1, 1};
    fn(m, CU_TENSOR_MAP_DATA_TYPE_BFLOAT16, 2, const_cast<void*>(p), dims, strides, box, es, CU_TENSOR_MAP_INTERLEAVE_NONE, sw, pr,
       CU_TENSOR_MAP_FLOAT_OOB_FILL_NONE);
}

}

extern "C" void kernel_launch(void* const* d_in, const int* in_sizes, int n_in, void* d_out, int out_size) {
    (void)in_sizes; (void)n_in; (void)out_size;
    static EncodeFn enc = nullptr;
    if (!enc) {
        void* fp = nullptr;
        cudaDriverEntryPointQueryResult qr;
        cudaGetDriverEntryPoint("cuTensorMapEncodeTiled", &fp, cudaEnableDefault, &qr);
        enc = (EncodeFn)fp;
        cudaFuncSetAttribute(fused_block_kernel, cudaFuncAttributeMaxDynamicSharedMemorySize, SM_TOTAL);
    }
    const __nv_bfloat16* x    = (const __nv_bfloat16*)d_in[0];
    const __nv_bfloat16* wo   = (const __nv_bfloat16*)d_in[4];
    const __nv_bfloat16* w2   = (const __nv_bfloat16*)d_in[8];
    const __nv_bfloat16* cvec = (const __nv_bfloat16*)d_in[9];
    CUtensorMap tk, tv, tq, tm, t1, t3, t1x, t3x;
    make_map(enc, &tk, d_in[1], DH, 2ull * HKV * SK, 64, TILE_KEYS, CU_TENSOR_MAP_SWIZZLE_128B, CU_TENSOR_MAP_L2_PROMOTION_L2_256B);
    make_map(enc, &tv, d_in[2], DH, 2ull * HKV * SK, 64, TILE_KEYS, CU_TENSOR_MAP_SWIZZLE_128B, CU_TENSOR_MAP_L2_PROMOTION_L2_256B);
    make_map(enc, &tq, d_in[3], NQ, D_, 32, 64, CU_TENSOR_MAP_SWIZZLE_64B, CU_TENSOR_MAP_L2_PROMOTION_L2_128B);
    make_map(enc, &tm, d_in[10], NMOD, D_, 32, 64, CU_TENSOR_MAP_SWIZZLE_64B, CU_TENSOR_MAP_L2_PROMOTION_L2_128B);
    make_map(enc, &t1, d_in[6], FF, D_, 32, 64, CU_TENSOR_MAP_SWIZZLE_64B, CU_TENSOR_MAP_L2_PROMOTION_L2_128B);
    make_map(enc, &t3, d_in[7], FF, D_, 32, 64, CU_TENSOR_MAP_SWIZZLE_64B, CU_TENSOR_MAP_L2_PROMOTION_L2_128B);
    make_map(enc, &t1x, d_in[6], FF, D_, 16, 192, CU_TENSOR_MAP_SWIZZLE_32B, CU_TENSOR_MAP_L2_PROMOTION_L2_128B);
    make_map(enc, &t3x, d_in[7], FF, D_, 16, 192, CU_TENSOR_MAP_SWIZZLE_32B, CU_TENSOR_MAP_L2_PROMOTION_L2_128B);
    fused_block_kernel<<<NCTA, NTHREADS, SM_TOTAL>>>(tk, tv, tq, tm, t1, t3, t1x, t3x, x, wo, w2, cvec, (const __nv_bfloat16*)d_in[10], (__nv_bfloat16*)d_out);
}
```

```cpp
#include <cuda_runtime.h>
#include <cuda.h>
#include <cuda_bf16.h>
#include <stdint.h>

namespace {

constexpr int D_   = 576;
constexpr int HKV  = 16;
constexpr int SK   = 8192;
constexpr int DH   = 128;
constexpr int FF   = 4608;
constexpr int NQ   = 4096;
constexpr int NMOD = 6 * D_;

constexpr int NCTA     = 128;
constexpr int NCW      = 9;
constexpr int NCT      = NCW * 32;
constexpr int NTHREADS = NCT + 32;
constexpr int KEYS_PER_CTA = SK / 4;
constexpr int TILE_KEYS = 64;
constexpr int NTILES   = KEYS_PER_CTA / TILE_KEYS;
constexpr int NITEMS   = 2 * NTILES;
constexpr int TILE_BYTES = TILE_KEYS * DH * 2;
constexpr int NRING = 8;
constexpr int BOX_BYTES = 64 * 64;
constexpr int PLANE_BYTES = 9 * BOX_BYTES;
constexpr int ROWB = D_ * 2;

#define TUNE_DH 2
#define TUNE_DB 4
#define TUNE_DWO 3
#define TUNE_DW 3
#define TUNE_DW2 8
#define TUNE_SLEEP 1000
#define TUNE_JM2 3
#define TUNE_PRE 26

constexpr int NM1CTA = 36;
constexpr int NMODCTA = NMOD / 32;
constexpr int NWO_CTA = 96;
constexpr int NRED_CTA = 72;

constexpr int SM_RING  = 0;
constexpr int SM_X     = NRING * TILE_BYTES;
constexpr int SM_XA    = SM_X;
constexpr int SM_XB    = SM_X + PLANE_BYTES;
constexpr int SM_XW2E  = SM_X + PLANE_BYTES;
constexpr int SM_W1B8  = 186880;
constexpr int SM_W3B8  = SM_W1B8 + BOX_BYTES;
constexpr int SM_W2G7  = SM_W3B8 + BOX_BYTES + 112;
constexpr int SM_MISC  = SM_X + 2 * PLANE_BYTES;
constexpr int SM_BAR   = SM_MISC;
constexpr int SM_SP    = SM_BAR + 320;
constexpr int HSTRIDE  = 584;
constexpr int SM_SC    = SM_SP + 8192;
constexpr int SM_HB    = SM_SC + 2 * HSTRIDE * 2;
constexpr int SM_RED   = SM_HB + 2 * HSTRIDE * 2;
constexpr int SM_MB    = SM_RED + 9 * 192 * 4;
constexpr int QSTRIDE  = 136;
constexpr int SM_QS    = SM_MB + D_ * 8;
constexpr int VPSTRIDE = 56;
constexpr int SM_VP    = SM_QS + 2 * QSTRIDE * 2;
constexpr int SM_ST    = SM_VP + 2 * VPSTRIDE * 2;
constexpr int SM_FAC   = SM_ST + 9 * 16;
constexpr int SM_HIST  = SM_FAC + 16;
constexpr int SM_TOTAL = SM_HIST + 64;
static_assert(SM_TOTAL <= 232448, "smem");
static_assert(SM_W2G7 + 4 * ROWB <= SM_MISC, "smem");
static_assert(SM_X + 8 * (6 * ROWB + 16) <= SM_W1B8, "smem");
static_assert((SM_ST % 16) == 0 && (SM_RED % 16) == 0 && (SM_MB % 16) == 0 && (SM_SP % 16) == 0, "align");

enum { B_KVFULL = 0, B_KVEMPTY = 8, B_WM = 16, B_WQ = 18, B_XFREE = 20, B_FAC = 21, B_MID = 22, B_W2 = 26, B_F = 30, B_COUNT = 39 };
constexpr int SM_W1 = SM_RING, SM_W3 = SM_RING + 32768, SM_W2 = SM_RING + 65536;

typedef unsigned long long u64;
struct __align__(128) Scratch {
    u64 h1[4][D_];
    u64 mod[2][D_][2];
    u64 q[2][NQ / 2];
    u64 ml[NCTA][16];
    u64 o[NCTA][2][8][8][2];
    u64 p2[NWO_CTA][D_][2];
    u64 x1[4][NRED_CTA][16];
    u64 p4[NCTA][D_][2];
    unsigned int epoch;
};
__device__ Scratch g_s;

#define TS(i)
#define TSL(i)

__device__ __forceinline__ uint32_t smem_u32(const void* p) { return (uint32_t)__cvta_generic_to_shared(p); }
__device__ __forceinline__ uint32_t pack_bf(float lo, float hi) {
    uint32_t r; asm("cvt.rn.bf16x2.f32 %0, %1, %2;" : "=r"(r) : "f"(hi), "f"(lo)); return r;
}
__device__ __forceinline__ float bf_lo(uint32_t v) { return __uint_as_float(v << 16); }
__device__ __forceinline__ float bf_hi(uint32_t v) { return __uint_as_float(v & 0xffff0000u); }
__device__ __forceinline__ uint32_t hsub2(uint32_t a, uint32_t b) { uint32_t r; asm("sub.rn.bf16x2 %0, %1, %2;" : "=r"(r) : "r"(a), "r"(b)); return r; }
__device__ __forceinline__ uint32_t hadd2(uint32_t a, uint32_t b) { uint32_t r; asm("add.rn.bf16x2 %0, %1, %2;" : "=r"(r) : "r"(a), "r"(b)); return r; }
__device__ __forceinline__ uint32_t hmul2(uint32_t a, uint32_t b) { uint32_t r; asm("mul.rn.bf16x2 %0, %1, %2;" : "=r"(r) : "r"(a), "r"(b)); return r; }
__device__ __forceinline__ float ex2(float x) { float r; asm("ex2.approx.ftz.f32 %0, %1;" : "=f"(r) : "f"(x)); return r; }
__device__ __forceinline__ float rcp(float x) { float r; asm("rcp.approx.ftz.f32 %0, %1;" : "=f"(r) : "f"(x)); return r; }
constexpr float LOG2E = 1.4426950408889634f;
__device__ __forceinline__ float silu_f(float x) { return x * rcp(1.0f + ex2(-x * LOG2E)); }

__device__ __forceinline__ void mbar_init(uint32_t bar, int cnt) { asm volatile("mbarrier.init.shared::cta.b64 [%0], %1;" ::"r"(bar), "r"(cnt)); }
__device__ __forceinline__ void mbar_expect_tx(uint32_t bar, uint32_t bytes) { asm volatile("mbarrier.arrive.expect_tx.shared::cta.b64 _, [%0], %1;" ::"r"(bar), "r"(bytes) : "memory"); }
__device__ __forceinline__ void mbar_arrive(uint32_t bar) { asm volatile("mbarrier.arrive.shared::cta.b64 _, [%0];" ::"r"(bar) : "memory"); }
__device__ __forceinline__ bool mbar_try(uint32_t bar, uint32_t parity) {
    uint32_t ok;
    asm volatile("{\n.reg .pred p;\nmbarrier.try_wait.parity.shared::cta.b64 p, [%1], %2;\nselp.u32 %0, 1, 0, p;\n}\n" : "=r"(ok) : "r"(bar), "r"(parity) : "memory");
    return ok != 0;
}
__device__ __forceinline__ bool mbar_test(uint32_t bar, uint32_t parity) {
    uint32_t ok;
    asm volatile("{\n.reg .pred p;\nmbarrier.test_wait.parity.shared::cta.b64 p, [%1], %2;\nselp.u32 %0, 1, 0, p;\n}\n" : "=r"(ok) : "r"(bar), "r"(parity) : "memory");
    return ok != 0;
}
__device__ __forceinline__ void mbar_wait(uint32_t bar, uint32_t parity) {
    uint32_t spins = 0;
    while (!mbar_try(bar, parity)) { if (++spins > (1u << 22)) __trap(); }
}
__device__ __forceinline__ void bulk_g2s(uint32_t dst, const void* src, uint32_t bytes, uint32_t bar, uint64_t pol) {
    asm volatile("cp.async.bulk.shared::cluster.global.mbarrier::complete_tx::bytes.L2::cache_hint [%0], [%1], %2, [%3], %4;" ::"r"(dst), "l"(src), "r"(bytes), "r"(bar), "l"(pol) : "memory");
}
__device__ __forceinline__ void tma2d(uint32_t dst, const CUtensorMap* map, int c0, int c1, uint32_t bar, uint64_t pol) {
    asm volatile("cp.async.bulk.tensor.2d.shared::cluster.global.mbarrier::complete_tx::bytes.L2::cache_hint [%0], [%1, {%2, %3}], [%4], %5;"
                 ::"r"(dst), "l"(map), "r"(c0), "r"(c1), "r"(bar), "l"(pol) : "memory");
}
__device__ __forceinline__ void cp16(uint32_t dst, const void* src) { asm volatile("cp.async.cg.shared.global [%0], [%1], 16;" ::"r"(dst), "l"(src) : "memory"); }
__device__ __forceinline__ void csync() { asm volatile("bar.sync 1, 288;" ::: "memory"); }
__device__ __forceinline__ void async8() { asm volatile("bar.sync 2, 256;" ::: "memory"); }

__device__ __forceinline__ void ldsm4(uint32_t (&r)[4], uint32_t addr) {
    asm volatile("ldmatrix.sync.aligned.m8n8.x4.shared.b16 {%0,%1,%2,%3}, [%4];" : "=r"(r[0]), "=r"(r[1]), "=r"(r[2]), "=r"(r[3]) : "r"(addr) : "memory");
}
__device__ __forceinline__ void ldsm4t(uint32_t (&r)[4], uint32_t addr) {
    asm volatile("ldmatrix.sync.aligned.m8n8.x4.trans.shared.b16 {%0,%1,%2,%3}, [%4];" : "=r"(r[0]), "=r"(r[1]), "=r"(r[2]), "=r"(r[3]) : "r"(addr) : "memory");
}
__device__ __forceinline__ void mma16816(float (&d)[4], uint32_t a0, uint32_t a1, uint32_t a2, uint32_t a3, uint32_t b0, uint32_t b1) {
    asm("mma.sync.aligned.m16n8k16.row.col.f32.bf16.bf16.f32 {%0,%1,%2,%3}, {%4,%5,%6,%7}, {%8,%9}, {%0,%1,%2,%3};"
                 : "+f"(d[0]), "+f"(d[1]), "+f"(d[2]), "+f"(d[3]) : "r"(a0), "r"(a1), "r"(a2), "r"(a3), "r"(b0), "r"(b1));
}
__device__ __forceinline__ uint32_t ldg32(const uint32_t* p) { uint32_t v; asm volatile("ld.global.nc.u32 %0, [%1];" : "=r"(v) : "l"(p)); return v; }
__device__ __forceinline__ uint32_t lds32(uint32_t addr) { uint32_t v; asm volatile("ld.shared.u32 %0, [%1];" : "=r"(v) : "r"(addr) : "memory"); return v; }
__device__ __forceinline__ float ldsf(uint32_t addr) { float v; asm volatile("ld.shared.f32 %0, [%1];" : "=f"(v) : "r"(addr) : "memory"); return v; }
__device__ __forceinline__ uint4 lds128(uint32_t addr) { uint4 v; asm volatile("ld.shared.v4.u32 {%0,%1,%2,%3}, [%4];" : "=r"(v.x), "=r"(v.y), "=r"(v.z), "=r"(v.w) : "r"(addr) : "memory"); return v; }
__device__ __forceinline__ void sts32(uint32_t addr, uint32_t v) { asm volatile("st.shared.u32 [%0], %1;" ::"r"(addr), "r"(v) : "memory"); }
__device__ __forceinline__ void sts64(uint32_t addr, uint32_t a, uint32_t b) { asm volatile("st.shared.v2.u32 [%0], {%1,%2};" ::"r"(addr), "r"(a), "r"(b) : "memory"); }
__device__ __forceinline__ void sts64f(uint32_t addr, float a, float b) { asm volatile("st.shared.v2.f32 [%0], {%1,%2};" ::"r"(addr), "f"(a), "f"(b) : "memory"); }
__device__ __forceinline__ void sts128(uint32_t addr, uint4 v) { asm volatile("st.shared.v4.u32 [%0], {%1,%2,%3,%4};" ::"r"(addr), "r"(v.x), "r"(v.y), "r"(v.z), "r"(v.w) : "memory"); }

__device__ __forceinline__ void st_pkt(u64* p, uint32_t v, uint32_t tag) {
    asm volatile("{\n.reg .b64 t;\nmov.b64 t, {%1,%2};\nst.relaxed.gpu.global.b64 [%0], t;\n}\n" ::"l"(p), "r"(v), "r"(tag) : "memory");
}
__device__ __forceinline__ void st_pkt2(u64* p, uint32_t a, uint32_t b, uint32_t tag) {
    asm volatile("{\n.reg .b64 t,u;\nmov.b64 t, {%1,%3};\nmov.b64 u, {%2,%3};\nst.relaxed.gpu.global.v2.b64 [%0], {t,u};\n}\n" ::"l"(p), "r"(a), "r"(b), "r"(tag) : "memory");
}
template <int OFF>
__device__ __forceinline__ void st_pkt2_if(bool p, const u64* base, float a, float b, uint32_t tag) {
    asm volatile("{\n.reg .pred p;\n.reg .b64 t,u;\nsetp.ne.u32 p, %4, 0;\nmov.b64 t, {%1,%3};\nmov.b64 u, {%2,%3};\n@p st.relaxed.gpu.global.v2.b64 [%0+%5], {t,u};\n}\n"
                 ::"l"(base), "r"(__float_as_uint(a)), "r"(__float_as_uint(b)), "r"(tag), "r"((uint32_t)p), "n"(OFF) : "memory");
}
__device__ __forceinline__ uint4 ld_pkt2(const u64* p) {
    uint4 v;
    asm volatile("{\n.reg .b64 t,u;\nld.relaxed.gpu.global.v2.b64 {t,u}, [%4];\nmov.b64 {%0,%1}, t;\nmov.b64 {%2,%3}, u;\n}\n"
                 : "=r"(v.x), "=r"(v.y), "=r"(v.z), "=r"(v.w) : "l"(p) : "memory");
    return v;
}
template <int N, int SLEEP = 0>
__device__ __forceinline__ void pollN(const u64* p, int stride, uint32_t tag, uint32_t (&a)[N], uint32_t (&b)[N]) {
    uint32_t spins = 0;
    while (true) {
        uint4 v[N];
#pragma unroll
        for (int i = 0; i < N; i++) v[i] = ld_pkt2(p + (size_t)i * stride);
        uint32_t bad = 0;
#pragma unroll
        for (int i = 0; i < N; i++) { bad |= (v[i].y ^ tag) | (v[i].w ^ tag); a[i] = v[i].x; b[i] = v[i].z; }
        if (!__any_sync(0xffffffffu, bad != 0)) break;
        if (SLEEP) __nanosleep(SLEEP);
        if (++spins > (1u << 22)) __trap();
    }
}

__device__ __forceinline__ void publish4(const float (&a)[4][4], int c, const u64* dst, uint32_t tag) {
    float v[4];
#pragma unroll
    for (int k = 0; k < 4; k++) {
        const float lo = (c & 1) ? a[1][k] : a[0][k], hi = (c & 1) ? a[3][k] : a[2][k];
        v[k] = (c & 2) ? hi : lo;
    }
    st_pkt2_if<0>(true, dst, v[0], v[1], tag);
    st_pkt2_if<128>(true, dst, v[2], v[3], tag);
}

__device__ __noinline__ void plane_gemv(uint32_t plane, uint32_t vec, uint32_t red, int warp, int lane) {
    const int g = lane >> 2, c = lane & 3, mi = lane >> 3, kap = lane & 7;
    const int rowl = kap + 8 * (mi >> 1);
    const uint32_t a0 = plane + warp * BOX_BYTES + rowl * 64 + ((((mi & 1)) ^ ((rowl >> 1) & 3)) << 4);
    const uint32_t bo = vec + (g & 1) * (HSTRIDE * 2) + warp * 128 + c * 4;
    float acc0[4] = {0.f, 0.f, 0.f, 0.f}, acc1[4] = {0.f, 0.f, 0.f, 0.f};
#pragma unroll
    for (int s = 0; s < 4; s++) {
        uint32_t x[4], y[4];
        ldsm4t(x, a0 + s * 1024);
        ldsm4t(y, (a0 ^ 32) + s * 1024);
        const uint32_t b0 = lds32(bo + s * 32), b1 = lds32(bo + s * 32 + 16);
        mma16816(acc0, x[0], x[1], x[2], x[3], b0, b1);
        mma16816(acc1, y[0], y[1], y[2], y[3], b0, b1);
    }
    if (c == 0) {
        const uint32_t r = red + warp * 768 + g * 8;
        sts64f(r, acc0[0], acc0[1]); sts64f(r + 64, acc0[2], acc0[3]);
        sts64f(r + 128, acc1[0], acc1[1]); sts64f(r + 192, acc1[2], acc1[3]);
    }
}
__device__ __forceinline__ float red9(uint32_t red, int idx) {
    float v[9];
#pragma unroll
    for (int w = 0; w < 9; w++) v[w] = ldsf(red + w * 768 + idx * 4);
    return ((v[0] + v[1]) + (v[2] + v[3])) + ((v[4] + v[5]) + (v[6] + v[7])) + v[8];
}

__device__ __forceinline__ void ln_stats(uint32_t xa, uint32_t xb, uint32_t sh, uint32_t st, int warp, int lane, uint32_t& mean2, float& r0, float& r1) {
    const float s0 = bf_lo(sh), s1 = bf_hi(sh);
    const float a0 = bf_lo(xa) - s0, a1 = bf_hi(xa) - s1, b0 = bf_lo(xb) - s0, b1 = bf_hi(xb) - s1;
    float u0 = a0 + b0, u1 = a1 + b1, q0 = a0 * a0 + b0 * b0, q1 = a1 * a1 + b1 * b1;
#pragma unroll
    for (int o = 16; o > 0; o >>= 1) {
        u0 += __shfl_xor_sync(0xffffffffu, u0, o); u1 += __shfl_xor_sync(0xffffffffu, u1, o);
        q0 += __shfl_xor_sync(0xffffffffu, q0, o); q1 += __shfl_xor_sync(0xffffffffu, q1, o);
    }
    if (lane == 0) sts128(st + warp * 16, make_uint4(__float_as_uint(u0), __float_as_uint(u1), __float_as_uint(q0), __float_as_uint(q1)));
    csync();
    uint4 v[9];
#pragma unroll
    for (int w = 0; w < 9; w++) v[w] = lds128(st + w * 16);
#define SUM9(f) ((((__uint_as_float(v[0].f) + __uint_as_float(v[1].f)) + (__uint_as_float(v[2].f) + __uint_as_float(v[3].f))) + \
                  ((__uint_as_float(v[4].f) + __uint_as_float(v[5].f)) + (__uint_as_float(v[6].f) + __uint_as_float(v[7].f)))) + __uint_as_float(v[8].f))
    u0 = SUM9(x) * (1.0f / D_); u1 = SUM9(y) * (1.0f / D_);
    q0 = SUM9(z); q1 = SUM9(w);
#undef SUM9
    const uint32_t var2 = pack_bf(fmaxf(fmaf(q0, 1.0f / D_, -u0 * u0), 0.f), fmaxf(fmaf(q1, 1.0f / D_, -u1 * u1), 0.f));
    mean2 = pack_bf(u0 + s0, u1 + s1);
    const uint32_t ve2 = pack_bf(bf_lo(var2) + 1e-5f, bf_hi(var2) + 1e-5f);
    float d0, d1;
    asm("sqrt.approx.ftz.f32 %0, %1;" : "=f"(d0) : "f"(bf_lo(ve2)));
    asm("sqrt.approx.ftz.f32 %0, %1;" : "=f"(d1) : "f"(bf_hi(ve2)));
    const uint32_t sd2 = pack_bf(d0, d1);
    r0 = rcp(bf_lo(sd2)); r1 = rcp(bf_hi(sd2));
}
__device__ __forceinline__ uint32_t modulate2(uint32_t x, uint32_t mean2, float r0, float r1, uint32_t shift, uint32_t onepscale) {
    const uint32_t d = hsub2(x, mean2);
    const uint32_t y = pack_bf(bf_lo(d) * r0, bf_hi(d) * r1);
    return hadd2(hmul2(y, onepscale), shift);
}
constexpr uint32_t ONE2 = 0x3f803f80u;

__global__ void __launch_bounds__(NTHREADS, 1)
fused_block_kernel(const __grid_constant__ CUtensorMap tm_k, const __grid_constant__ CUtensorMap tm_v,
                   const __grid_constant__ CUtensorMap tm_wq, const __grid_constant__ CUtensorMap tm_wm,
                   const __grid_constant__ CUtensorMap tm_w1, const __grid_constant__ CUtensorMap tm_w3,
                   const __grid_constant__ CUtensorMap tm_w1x, const __grid_constant__ CUtensorMap tm_w3x,
                   const __nv_bfloat16* __restrict__ x, const __nv_bfloat16* __restrict__ wo, const __nv_bfloat16* __restrict__ w2,
                   const __nv_bfloat16* __restrict__ cvec, const __nv_bfloat16* __restrict__ wmod, __nv_bfloat16* __restrict__ out) {
    extern __shared__ __align__(1024) uint8_t smem[];
    int tid, cta;
    uint32_t sb;
    Scratch* gs;
    asm volatile("mov.u32 %0, %1;" : "=r"(tid) : "r"(threadIdx.x));
    asm volatile("mov.u32 %0, %1;" : "=r"(cta) : "r"(blockIdx.x));
    asm volatile("mov.u32 %0, %1;" : "=r"(sb) : "r"(smem_u32(smem)));
    asm volatile("mov.u64 %0, %1;" : "=l"(gs) : "l"(&g_s));
    const int warp = tid >> 5, lane = tid & 31;
    auto BAR = [&](int i) { return sb + SM_BAR + 8 * i; };

    const int bb = cta >> 6, kvh = (cta >> 2) & 15;
    const bool typeA = cta < 32;
    const int wj = cta - 32;
    const int nO = typeA ? 0 : (wj < 32 ? 2 : 3);
    const int o_r0 = wj < 32 ? 32 * wj : 1024 + 48 * (wj - 32);
    const bool m1 = cta < NM1CTA, m2 = cta >= NM1CTA && cta < NMODCTA;

    TS(0);
    const int krow0 = cta * KEYS_PER_CTA;
    const uint32_t* x32 = reinterpret_cast<const uint32_t*>(x);
    uint64_t pol;
    asm volatile("createpolicy.fractional.L2::evict_first.b64 %0, 1.0;" : "=l"(pol));
    if (tid == NCT) {
        mbar_init(BAR(B_WQ), 1); mbar_init(BAR(B_WQ + 1), 1); mbar_init(BAR(B_KVFULL), 1);
        asm volatile("fence.mbarrier_init.release.cluster;" ::: "memory");
        TSL(22);
        mbar_expect_tx(BAR(B_WQ), 5 * BOX_BYTES);
#pragma unroll
        for (int i = 0; i < 5; i++) tma2d(sb + SM_XB + (i < 4 ? i : 8) * BOX_BYTES, &tm_wq, cta * 32, (i < 4 ? i : 8) * 64, BAR(B_WQ), pol);
        mbar_expect_tx(BAR(B_WQ + 1), 4 * BOX_BYTES);
#pragma unroll
        for (int i = 4; i < 8; i++) tma2d(sb + SM_XB + i * BOX_BYTES, &tm_wq, cta * 32, i * 64, BAR(B_WQ + 1), pol);
        mbar_expect_tx(BAR(B_KVFULL), TILE_BYTES);
        tma2d(sb + SM_RING, &tm_k, 0, krow0, BAR(B_KVFULL), pol);
        tma2d(sb + SM_RING + 8192, &tm_k, 64, krow0, BAR(B_KVFULL), pol);
#pragma unroll
        for (int i = 1; i < 8; i++) mbar_init(BAR(B_KVFULL + i), 1);
#pragma unroll
        for (int i = 0; i < 8; i++) mbar_init(BAR(B_KVEMPTY + i), 8);
        mbar_init(BAR(B_WM), 1); mbar_init(BAR(B_WM + 1), 1);
#pragma unroll
        for (int i = B_FAC; i < B_COUNT; i++) mbar_init(BAR(i), 1);
        mbar_init(BAR(B_XFREE), NCW);
        asm volatile("fence.mbarrier_init.release.cluster;" ::: "memory");
    }
    uint32_t tag, c0 = 0, c1 = 0, u0 = 0, u1 = 0, z0 = 0, z1 = 0, xo0 = 0, xo1 = 0;
    asm volatile("ld.relaxed.gpu.global.u32 %0, [%1];" : "=r"(tag) : "l"(&gs->epoch) : "memory");
    if (cta < NMODCTA && warp < NCW) {
        const uint32_t* c32 = reinterpret_cast<const uint32_t*>(cvec);
        c0 = ldg32(c32 + tid); c1 = ldg32(c32 + D_ / 2 + tid);
        if (m1) {
            u0 = ldg32(x32 + tid); u1 = ldg32(x32 + D_ / 2 + tid);
            z0 = ldg32(x32); z1 = ldg32(x32 + D_ / 2);
            xo0 = ldg32(x32 + cta * 8 + (lane >> 2)); xo1 = ldg32(x32 + D_ / 2 + cta * 8 + (lane >> 2));
            const int g = lane >> 2, c = lane & 3;
            const char* src = reinterpret_cast<const char*>(wmod) + (size_t)(warp * 64 + g) * (NMOD * 2) + (c & 1) * (D_ * 2) + cta * 32 + (c >> 1) * 16;
            const uint32_t dst = sb + SM_XA + (warp * 64 + g) * 64 + ((c ^ ((g >> 1) & 3)) << 4);
#pragma unroll
            for (int i = 0; i < 8; i++) cp16(dst + i * 512, src + (size_t)i * 8 * (NMOD * 2));
        }
    }
    if (warp == NCW) {
        __syncwarp();
        asm volatile("bar.arrive 0, 320;" ::: "memory");
        if (lane != 0) return;
        const uint32_t hist = sb + SM_HIST;
        sts32(hist, BAR(B_WQ)); sts32(hist + 4, BAR(B_WQ + 1)); sts32(hist + 8, BAR(B_KVFULL));
        int n = 3;
        auto window = [&](int D) {
            if (n >= D) { const uint32_t h = lds32(hist + ((n - D) & 15) * 4); mbar_wait(h & ~1u, h & 1u); }
        };
        auto issued = [&](uint32_t bar, uint32_t par) { sts32(hist + (n & 15) * 4, bar | par); n++; };
        auto plane_half = [&](const CUtensorMap* map, uint32_t base, uint32_t box8, int bar, int half, int D) {
            window(D);
            mbar_expect_tx(BAR(bar + half), (half ? 4 : 5) * BOX_BYTES);
#pragma unroll
            for (int i = 0; i < 4; i++) tma2d(base + (half * 4 + i) * BOX_BYTES, map, cta * 32, (half * 4 + i) * 64, BAR(bar + half), pol);
            if (!half) tma2d(box8, map, cta * 32, 512, BAR(bar), pol);
            issued(BAR(bar + half), 0);
        };
        auto rows8 = [&](const __nv_bfloat16* w, int row0, int rpg, uint32_t base, uint32_t g7, uint32_t bar, int g0, int ng) {
            const uint32_t gb = rpg * ROWB;
#pragma unroll 1
            for (int gi = g0; gi < g0 + ng; gi++)
                bulk_g2s(gi < 7 ? base + gi * (gb + 16) : g7, reinterpret_cast<const char*>(w) + (size_t)row0 * ROWB + (size_t)gi * gb, gb, bar, pol);
        };
#pragma unroll 1
        for (int j = 1; j < NITEMS; j++) {
            const int s = j & 7;
            int D = TUNE_DB;
            if (j >= 8) mbar_wait(BAR(B_KVEMPTY + s), ((j >> 3) - 1) & 1);
            else if (!mbar_test(BAR(B_KVEMPTY), 0)) D = TUNE_DH;
            window(D);
            mbar_expect_tx(BAR(B_KVFULL + s), TILE_BYTES);
            const CUtensorMap* map = j < NTILES ? &tm_k : &tm_v;
            tma2d(sb + SM_RING + s * TILE_BYTES, map, 0, krow0 + (j & 31) * TILE_KEYS, BAR(B_KVFULL + s), pol);
            tma2d(sb + SM_RING + s * TILE_BYTES + 8192, map, 64, krow0 + (j & 31) * TILE_KEYS, BAR(B_KVFULL + s), pol);
            issued(BAR(B_KVFULL + s), (j >> 3) & 1);
            if (m2 && (j == TUNE_JM2 || j == TUNE_JM2 + 1)) plane_half(&tm_wm, sb + SM_XA, sb + SM_XA + 8 * BOX_BYTES, B_WM, j - TUNE_JM2, D);
        }
        TSL(16);
        mbar_wait(BAR(B_XFREE), 0);
        if (!typeA) {
#pragma unroll 1
            for (int h = 0; h < 4; h++) {
                window(TUNE_DWO);
                mbar_expect_tx(BAR(B_MID + h), 4 * nO * ROWB);
                rows8(wo, o_r0, 2 * nO, sb + SM_X, sb + SM_X + 7 * (2 * nO * ROWB + 16), BAR(B_MID + h), 2 * h, 2);
                issued(BAR(B_MID + h), 0);
            }
        }
        bool open = false;
        uint32_t spins = 0;
        auto tail_window = [&]() {
            while (!open) {
                const uint32_t h = lds32(hist + ((n - TUNE_DW) & 15) * 4);
                if (mbar_test(h & ~1u, h & 1u)) return;
                const uint4 v = ld_pkt2(&gs->x1[cta & 3][(cta * 5) % NRED_CTA][0]);
                open = v.y == tag + 1;
                if (++spins > (1u << 22)) __trap();
            }
            window(TUNE_DW2);
        };
#pragma unroll 1
        for (int i = 0; i < 9; i++) {
            const int bx = i == 0 ? 8 : i - 1;
            if (i == 1) { mbar_wait(BAR(B_KVEMPTY + 0), 1); mbar_wait(BAR(B_KVEMPTY + 2), 1); }
            if (i == 5) { mbar_wait(BAR(B_KVEMPTY + 1), 1); mbar_wait(BAR(B_KVEMPTY + 3), 1); }
            tail_window();
            mbar_expect_tx(BAR(B_F + bx), 2 * BOX_BYTES);
            tma2d(sb + (i ? SM_W1 + bx * BOX_BYTES : SM_W1B8), &tm_w1, cta * 32, bx * 64, BAR(B_F + bx), pol);
            tma2d(sb + (i ? SM_W3 + bx * BOX_BYTES : SM_W3B8), &tm_w3, cta * 32, bx * 64, BAR(B_F + bx), pol);
            issued(BAR(B_F + bx), 0);
            if (typeA && i < 4) {
                tail_window();
                mbar_expect_tx(BAR(B_MID + i), i < 3 ? 2 * 6144 : 16 * ROWB);
                if (i < 3) {
                    tma2d(sb + SM_XA + i * 6144, &tm_w1x, NQ + 16 * cta, i * 192, BAR(B_MID + i), pol);
                    tma2d(sb + SM_XA + 18432 + i * 6144, &tm_w3x, NQ + 16 * cta, i * 192, BAR(B_MID + i), pol);
                } else rows8(w2, NQ + 16 * cta, 2, sb + SM_XW2E, sb + SM_XW2E + 7 * (2 * ROWB + 16), BAR(B_MID + 3), 0, 8);
                issued(BAR(B_MID + i), 0);
            }
        }
        mbar_wait(BAR(B_KVEMPTY + 4), 1);
        mbar_wait(BAR(B_KVEMPTY + 5), 1);
#pragma unroll 1
        for (int h = 0; h < 4; h++) {
            tail_window();
            mbar_expect_tx(BAR(B_W2 + h), 8 * ROWB);
            rows8(w2, cta * 32, 4, sb + SM_W2, sb + SM_W2G7, BAR(B_W2 + h), 2 * h, 2);
            issued(BAR(B_W2 + h), 0);
        }
        TSL(17);
        return;
    }

    const int g = lane >> 2, c = lane & 3, mi = lane >> 3, kap = lane & 7;
    const int whalf = (warp >> 2) & 1;
    const int rowl = kap + 8 * (mi >> 1);
    const uint32_t sw64 = (rowl >> 1) & 3;
    const uint32_t hbo = sb + SM_HB + (g & 1) * (HSTRIDE * 2) + warp * 128 + c * 4;
    const uint32_t redw = sb + SM_RED + warp * 768 + g * 8;
    if (warp == 0) {
        st_pkt(&gs->q[lane >> 4][cta * 16 + (lane & 15)], 0u, 0u);
        if (m1) st_pkt2(&gs->h1[lane >> 3][cta * 16 + (lane & 7) * 2], 0u, 0u, 0u);
    }
    if (cta < NMODCTA) {
        sts32(sb + SM_SC + tid * 4, pack_bf(silu_f(bf_lo(c0)), silu_f(bf_hi(c0))));
        sts32(sb + SM_SC + HSTRIDE * 2 + tid * 4, pack_bf(silu_f(bf_lo(c1)), silu_f(bf_hi(c1))));
        if (m1) {
            uint32_t mean2; float r0, r1;
            ln_stats(__byte_perm(u0, u1, 0x5410), __byte_perm(u0, u1, 0x7632), __byte_perm(z0, z1, 0x5410), sb + SM_ST, warp, lane, mean2, r0, r1);
            asm volatile("cp.async.wait_all;" ::: "memory");
            __syncwarp();
            TSL(70 + warp);
            plane_gemv(sb + SM_XA, sb + SM_SC, sb + SM_RED, warp, lane);
            csync();
            if (warp == 0) {
                const int idx = (lane >> 4) * 32 + (lane & 15);
                const float sa = red9(sb + SM_RED, idx), ca = red9(sb + SM_RED, idx + 16);
                const uint32_t sa2 = pack_bf(sa, __shfl_xor_sync(0xffffffffu, sa, 1)), ca2 = pack_bf(ca, __shfl_xor_sync(0xffffffffu, ca, 1));
                const uint32_t xo = __byte_perm(xo0, xo1, (lane & 2) ? 0x7632 : 0x5410);
                const uint32_t h = modulate2(xo, mean2, r0, r1, sa2, hadd2(ca2, ONE2));
                const uint32_t hp = __shfl_sync(0xffffffffu, h, (lane & 7) * 4), hq = __shfl_sync(0xffffffffu, h, (lane & 7) * 4 + 2);
                st_pkt2(&gs->h1[lane >> 3][cta * 16 + (lane & 7) * 2], hp, hq, tag + 1);
            }
            TS(2);
        }
    }
    tag += 1;
    asm volatile("bar.sync 0, 320;" ::: "memory");
    TS(1);
    {
        uint32_t af[4][2][4];
        const uint32_t a0 = sb + SM_XB + warp * BOX_BYTES + rowl * 64 + (((mi & 1) ^ sw64) << 4);
        mbar_wait(BAR(B_WQ + whalf), 0);
        TS(21);
#pragma unroll
        for (int s = 0; s < 4; s++) { ldsm4t(af[s][0], a0 + s * 1024); ldsm4t(af[s][1], (a0 ^ 32) + s * 1024); }
        uint32_t ha[1], hb[1];
        pollN<1>(&gs->h1[cta & 3][2 * tid], 0, tag, ha, hb);
        sts32(sb + SM_HB + tid * 4, __byte_perm(ha[0], hb[0], 0x5410));
        sts32(sb + SM_HB + HSTRIDE * 2 + tid * 4, __byte_perm(ha[0], hb[0], 0x7632));
        __syncwarp();
        TS(3);
        float acc0[4] = {0.f, 0.f, 0.f, 0.f}, acc1[4] = {0.f, 0.f, 0.f, 0.f};
#pragma unroll
        for (int s = 0; s < 4; s++) {
            const uint32_t b0 = lds32(hbo + s * 32), b1 = lds32(hbo + s * 32 + 16);
            mma16816(acc0, af[s][0][0], af[s][0][1], af[s][0][2], af[s][0][3], b0, b1);
            mma16816(acc1, af[s][1][0], af[s][1][1], af[s][1][2], af[s][1][3], b0, b1);
        }
        if (c == 0) {
            sts64f(redw, acc0[0], acc0[1]); sts64f(redw + 64, acc0[2], acc0[3]);
            sts64f(redw + 128, acc1[0], acc1[1]); sts64f(redw + 192, acc1[2], acc1[3]);
        }
        csync();
        if (warp == 0) {
            const int idx = (lane & 15) * 4 + (lane >> 4);
            st_pkt(&gs->q[lane >> 4][cta * 16 + (lane & 15)], pack_bf(red9(sb + SM_RED, idx), red9(sb + SM_RED, idx + 2)), tag);
        }
    }
    TS(4);
    auto mod2_phase = [&]() {
        if (m2) {
            mbar_wait(BAR(B_WM + whalf), 0);
            plane_gemv(sb + SM_XA, sb + SM_SC, sb + SM_RED, warp, lane);
            csync();
            if (tid < 64) {
                const float v = red9(sb + SM_RED, tid);
                const float o = __shfl_xor_sync(0xffffffffu, v, 1);
                const int which = cta / 18, i = (cta % 18) * 32 + (tid >> 1);
                if ((tid & 1) == 0) st_pkt(&gs->mod[(which == 2 || which == 5) ? 1 : 0][i][which >> 2], pack_bf(v, o), tag);
            }
        }
        asm volatile("fence.proxy.async.shared::cta;" ::: "memory");
        __syncwarp();
        if (lane == 0) mbar_arrive(BAR(B_XFREE));
    };

    const bool reducer = cta < NRED_CTA;
    const int rcol = cta * 8 + (lane & 3) * 2;
    uint32_t gav[2] = {0, 0}, gbv[2] = {0, 0}, xin[2] = {0, 0};
    auto preload_tail = [&]() {
        if (reducer && warp == 0) {
            const uint32_t u0 = __ldg(x32 + (rcol >> 1)), u1 = __ldg(x32 + ((D_ + rcol) >> 1));
            xin[0] = __byte_perm(u0, u1, 0x5410); xin[1] = __byte_perm(u0, u1, 0x7632);
            pollN<2>(&gs->mod[1][rcol][0], 2, tag, gav, gbv);
        }
    };

    if (warp == 8) {
#pragma unroll 2
        for (int i = lane; i < D_; i += 32) {
            st_pkt2(&gs->p4[cta][i][0], 0u, 0u, 0u);
            if (!typeA) st_pkt2(&gs->p2[wj][i][0], 0u, 0u, 0u);
            if (i < DH) st_pkt2(&gs->o[cta][0][0][0][0] + 2 * i, 0u, 0u, 0u);
        }
        asm volatile("bar.sync 3, 64;" ::: "memory");
        mod2_phase();
#pragma unroll 1
        for (int i = lane; i < D_; i += 64) {
            uint32_t s2[2], c2[2];
            pollN<2, TUNE_SLEEP>(&gs->mod[0][i][0], 64, tag, s2, c2);
            sts64(sb + SM_MB + i * 8, s2[0], hadd2(c2[0], ONE2));
            sts64(sb + SM_MB + (i + 32) * 8, s2[1], hadd2(c2[1], ONE2));
        }
        {
            uint32_t a[1], e[1];
            pollN<1, TUNE_SLEEP>(&gs->ml[(cta & ~3) + ((lane >> 1) & 3)][(lane & 1) * 2], 0, tag, a, e);
            const float m = __uint_as_float(a[0]);
            float M = fmaxf(m, __shfl_xor_sync(0xffffffffu, m, 2));
            M = fmaxf(M, __shfl_xor_sync(0xffffffffu, M, 4));
            const float w = ex2((m - M) * LOG2E);
            float L = w * __uint_as_float(e[0]);
            L += __shfl_xor_sync(0xffffffffu, L, 2);
            L += __shfl_xor_sync(0xffffffffu, L, 4);
            if ((lane >> 1) == (cta & 3)) sts32(sb + SM_FAC + (lane & 1) * 4, __float_as_uint(w / L));
        }
        __syncwarp();
        if (lane == 0) mbar_arrive(BAR(B_FAC));
        preload_tail();
    } else {
        if (tid < 64) {
            uint32_t a[1], e[1];
            pollN<1>(&gs->q[bb][kvh * 128 + tid * 2], 0, tag, a, e);
            sts64(sb + SM_QS + (tid >> 5) * (QSTRIDE * 2) + (tid & 31) * 8, a[0], e[0]);
        }
        async8();
        if (warp == 7) asm volatile("bar.arrive 3, 64;" ::: "memory");
        TS(5);
        uint32_t qa[8][2];
#pragma unroll
        for (int s = 0; s < 8; s++) {
            const uint32_t a = sb + SM_QS + (g & 1) * (QSTRIDE * 2) + (16 * s + 2 * c) * 2;
            qa[s][0] = lds32(a); qa[s][1] = lds32(a + 16);
        }
        constexpr float SCALE = 0.08838834764831845f;
        float mrun = -INFINITY;
        const uint32_t koff = (8 * warp + kap) * 128 + ((mi ^ kap) << 4);
        const uint32_t spw = sb + SM_SP + (g & 1) * 128 + c * 32;
#pragma unroll 1
        for (int t = 0; t < NTILES; t++) {
            const int s = t & 7;
            mbar_wait(BAR(B_KVFULL + s), (t >> 3) & 1);
            if ((t & 3) == 0) TS(24 + (t >> 2));
            float s0[4] = {0.f, 0.f, 0.f, 0.f}, s1[4] = {0.f, 0.f, 0.f, 0.f};
            const uint32_t ka = sb + SM_RING + s * TILE_BYTES + koff;
#pragma unroll
            for (int i = 0; i < 4; i++) {
                uint32_t u[4];
                ldsm4(u, (ka ^ ((i & 1) << 6)) + (i >> 1) * 8192);
                mma16816(s0, qa[2 * i][0], 0u, qa[2 * i][1], 0u, u[0], u[1]);
                mma16816(s1, qa[2 * i + 1][0], 0u, qa[2 * i + 1][1], 0u, u[2], u[3]);
            }
            __syncwarp();
            if (lane == 0) mbar_arrive(BAR(B_KVEMPTY + s));
            const uint32_t d0 = pack_bf(s0[0] + s1[0], s0[1] + s1[1]);
            const uint32_t e0 = pack_bf(bf_lo(d0) * SCALE, bf_hi(d0) * SCALE);
            mrun = fmaxf(mrun, fmaxf(bf_lo(e0), bf_hi(e0)));
            if (g < 2) sts32(spw + t * 256 + warp * 4, e0);
        }
        TS(6);
        mrun = fmaxf(mrun, __shfl_xor_sync(0xffffffffu, mrun, 1));
        mrun = fmaxf(mrun, __shfl_xor_sync(0xffffffffu, mrun, 2));
        if (lane == 0 || lane == 4) sts32(sb + SM_ST + (g * 8 + warp) * 4, __float_as_uint(mrun));
        async8();
        {
            const int h = (tid >> 2) & 1;
            const uint4 m0 = lds128(sb + SM_ST + h * 32), m1v = lds128(sb + SM_ST + h * 32 + 16);
            const float M = fmaxf(fmaxf(fmaxf(__uint_as_float(m0.x), __uint_as_float(m0.y)), fmaxf(__uint_as_float(m0.z), __uint_as_float(m0.w))),
                                  fmaxf(fmaxf(__uint_as_float(m1v.x), __uint_as_float(m1v.y)), fmaxf(__uint_as_float(m1v.z), __uint_as_float(m1v.w))));
            float l = 0.f;
#pragma unroll
            for (int k = 0; k < 2; k++) {
                uint4 v = lds128(sb + SM_SP + tid * 32 + k * 16);
                uint32_t* w = reinterpret_cast<uint32_t*>(&v);
#pragma unroll
                for (int i = 0; i < 4; i++) {
                    const float p0 = ex2((bf_lo(w[i]) - M) * LOG2E), p1 = ex2((bf_hi(w[i]) - M) * LOG2E);
                    l += p0 + p1;
                    w[i] = pack_bf(p0, p1);
                }
                sts128(sb + SM_SP + tid * 32 + k * 16, v);
            }
            l += __shfl_xor_sync(0xffffffffu, l, 1); l += __shfl_xor_sync(0xffffffffu, l, 2);
            l += __shfl_xor_sync(0xffffffffu, l, 8); l += __shfl_xor_sync(0xffffffffu, l, 16);
            if (lane == 0 || lane == 4) sts32(sb + SM_ST + 64 + (h * 8 + warp) * 4, __float_as_uint(l));
            async8();
            if (tid == 0 || tid == 4) {
                const uint4 l0 = lds128(sb + SM_ST + 64 + h * 32), l1 = lds128(sb + SM_ST + 64 + h * 32 + 16);
                const float L = ((__uint_as_float(l0.x) + __uint_as_float(l0.y)) + (__uint_as_float(l0.z) + __uint_as_float(l0.w))) +
                                ((__uint_as_float(l1.x) + __uint_as_float(l1.y)) + (__uint_as_float(l1.z) + __uint_as_float(l1.w)));
                st_pkt2(&gs->ml[cta][h * 2], __float_as_uint(M), __float_as_uint(L), tag);
            }
            __syncwarp();
        }
        mod2_phase();
        TS(7);
        float oacc0[4] = {0.f, 0.f, 0.f, 0.f}, oacc1[4] = {0.f, 0.f, 0.f, 0.f};
        float f0 = 0.f, f1 = 0.f;
        const uint32_t voff = (warp >> 2) * 8192 + rowl * 128 + (((2 * (warp & 3) + (mi & 1)) ^ kap) << 4);
        const u64* odst = &gs->o[cta][c & 1][warp][g][0];
#pragma unroll 1
        for (int t = 0; t < NTILES; t++) {
            const int s = t & 7;
            uint4 pb[2];
            pb[0] = lds128(spw + t * 256); pb[1] = lds128(spw + t * 256 + 16);
            mbar_wait(BAR(B_KVFULL + s), (t >> 3) & 1);
            if ((t & 3) == 3) TS(32 + (t >> 2));
            const uint32_t va = sb + SM_RING + s * TILE_BYTES + voff;
#pragma unroll
            for (int i = 0; i < 2; i++) {
                uint32_t u[4], v[4];
                ldsm4t(u, va + (2 * i) * 2048);
                ldsm4t(v, va + (2 * i + 1) * 2048);
                mma16816(oacc0, u[0], u[1], u[2], u[3], pb[i].x, pb[i].y);
                mma16816(oacc1, v[0], v[1], v[2], v[3], pb[i].z, pb[i].w);
            }
            __syncwarp();
            if (lane == 0) mbar_arrive(BAR(B_KVEMPTY + s));
            if (t == TUNE_PRE) {
                preload_tail();
                mbar_wait(BAR(B_FAC), 0);
                f0 = ldsf(sb + SM_FAC); f1 = ldsf(sb + SM_FAC + 4);
            }
        }
        TS(8);
        {
            const float f = (c & 1) ? f1 : f0;
            const float u = (c & 1) ? oacc0[1] + oacc1[1] : oacc0[0] + oacc1[0], v = (c & 1) ? oacc0[3] + oacc1[3] : oacc0[2] + oacc1[2];
            st_pkt2_if<0>(c < 2, odst, u * f, v * f, tag);
        }
    }
    TS(9);
    const uint32_t vpb = sb + SM_VP + (g & 1) * (VPSTRIDE * 2) + c * 4;
    if (nO > 0) {
        const int j = lane & 7, s = (lane >> 3) & 3, b = warp & 1, u = warp >> 1;
        const u64* dst = &gs->p2[wj][warp * 64 + c * 16 + g][0];
        if (u < nO) {
            const int row = o_r0 + 16 * u;
            const int hq = row >> 7;
            const int r = 16 * u + j + 8 * (s & 1);
            const int grp = nO == 3 ? (r * 43) >> 8 : r >> 2, rr = r - grp * 2 * nO;
            const uint32_t vd = sb + SM_VP + b * (VPSTRIDE * 2) + (16 * (rr >> 1) + (rr & 1) * 8 + grp) * 2;
            uint32_t a[1], e[1];
            pollN<1>(&gs->o[b * 64 + (hq >> 1) * 4 + s][hq & 1][(row >> 4) & 7][j][0], 0, tag, a, e);
            float o0 = __uint_as_float(a[0]), o1 = __uint_as_float(e[0]);
            o0 += __shfl_xor_sync(0xffffffffu, o0, 8); o1 += __shfl_xor_sync(0xffffffffu, o1, 8);
            o0 += __shfl_xor_sync(0xffffffffu, o0, 16); o1 += __shfl_xor_sync(0xffffffffu, o1, 16);
            const uint32_t pk = pack_bf(o0, o1);
            if (s < 2) asm volatile("st.shared.b16 [%0], %1;" ::"r"(vd), "h"((unsigned short)(s ? pk >> 16 : pk)) : "memory");
        }
        uint32_t wof[4][3][4];
        {
            const uint32_t ab = sb + SM_X + kap * (2 * nO * ROWB + 16) + (mi >> 1) * ROWB + (mi & 1) * 16 + warp * 128;
#pragma unroll
            for (int i = 0; i < 4; i++) mbar_wait(BAR(B_MID + i), 0);
#pragma unroll
            for (int i = 0; i < 4; i++) {
                ldsm4t(wof[i][0], ab + i * 32);
                ldsm4t(wof[i][1], ab + i * 32 + 2 * ROWB);
                ldsm4t(wof[i][2], ab + i * 32 + 4 * ROWB);
            }
        }
        csync();
        TS(10);
        uint32_t b0[3], b1[3];
#pragma unroll
        for (int k = 0; k < 3; k++) { b0[k] = lds32(vpb + k * 32); b1[k] = lds32(vpb + k * 32 + 16); }
        float acc[4][4];
#pragma unroll
        for (int i = 0; i < 4; i++) { acc[i][0] = acc[i][1] = acc[i][2] = acc[i][3] = 0.f; mma16816(acc[i], wof[i][0][0], wof[i][0][1], wof[i][0][2], wof[i][0][3], b0[0], b1[0]); }
#pragma unroll
        for (int i = 0; i < 4; i++) mma16816(acc[i], wof[i][1][0], wof[i][1][1], wof[i][1][2], wof[i][1][3], b0[1], b1[1]);
        if (nO == 3) {
#pragma unroll
            for (int i = 0; i < 4; i++) mma16816(acc[i], wof[i][2][0], wof[i][2][1], wof[i][2][2], wof[i][2][3], b0[2], b1[2]);
        }
        publish4(acc, c, dst, tag);
        TSL(80 + warp);
    }
    TS(11);
    uint32_t x1v[2] = {0, 0};
    auto sum8 = [&](uint32_t (&r)[2]) {
        float v[4] = {0.f, 0.f, 0.f, 0.f}, w[4] = {0.f, 0.f, 0.f, 0.f};
#pragma unroll
        for (int k = 0; k < 8; k += 2) {
            const uint4 a = lds128(sb + SM_SP + k * 64 + (lane & 3) * 16), e = lds128(sb + SM_SP + k * 64 + 64 + (lane & 3) * 16);
            v[0] += __uint_as_float(a.x); v[1] += __uint_as_float(a.y); v[2] += __uint_as_float(a.z); v[3] += __uint_as_float(a.w);
            w[0] += __uint_as_float(e.x); w[1] += __uint_as_float(e.y); w[2] += __uint_as_float(e.z); w[3] += __uint_as_float(e.w);
        }
        r[0] = pack_bf(v[0] + w[0], v[1] + w[1]); r[1] = pack_bf(v[2] + w[2], v[3] + w[3]);
    };
    if (reducer && warp < 8) {
        uint32_t a[3], e[3];
        pollN<3>(&gs->p2[warp * 12 + (lane >> 3)][cta * 8 + (lane & 7)][0], 4 * D_ * 2, tag, a, e);
        float v0 = (__uint_as_float(a[0]) + __uint_as_float(a[1])) + __uint_as_float(a[2]);
        float v1 = (__uint_as_float(e[0]) + __uint_as_float(e[1])) + __uint_as_float(e[2]);
        v0 += __shfl_xor_sync(0xffffffffu, v0, 8); v1 += __shfl_xor_sync(0xffffffffu, v1, 8);
        v0 += __shfl_xor_sync(0xffffffffu, v0, 16); v1 += __shfl_xor_sync(0xffffffffu, v1, 16);
        if (lane < 8) sts64f(sb + SM_SP + warp * 64 + lane * 8, v0, v1);
        if (warp == 0) {
            TS(12);
            async8();
            TS(13);
            uint32_t r[2];
            sum8(r);
            x1v[0] = hadd2(xin[0], hmul2(gav[0], r[0])); x1v[1] = hadd2(xin[1], hmul2(gav[1], r[1]));
            if (lane < 16) st_pkt2(&gs->x1[lane >> 2][cta][(lane & 3) * 2], x1v[0], x1v[1], tag);
            __syncwarp();
        } else {
            asm volatile("bar.arrive 2, 256;" ::: "memory");
        }
    }
    TSL(60 + warp);
    {
        const uint32_t pb = ((mi & 1) ? (warp < 8 ? sb + SM_W3 + warp * BOX_BYTES : sb + SM_W3B8)
                                      : (warp < 8 ? sb + SM_W1 + warp * BOX_BYTES : sb + SM_W1B8)) + rowl * 64 + (sw64 << 4);
        const uint32_t pe = sb + SM_XA + (mi & 1) * 18432 + (warp * 64 + rowl) * 32 + (((rowl >> 2) & 1) << 4);
        const uint32_t ab = (kap < 7 ? sb + SM_W2 + kap * (4 * ROWB + 16) : sb + SM_W2G7) + (mi >> 1) * ROWB + (mi & 1) * 16 + warp * 128;
        const uint32_t aeb = sb + SM_XW2E + kap * (2 * ROWB + 16) + (mi >> 1) * ROWB + (mi & 1) * 16 + warp * 128;
        const u64* dst = &gs->p4[cta][warp * 64 + c * 16 + g][0];
        const int ar = tid >> 1;
        const uint32_t ared = sb + SM_RED + ((ar >> 3) * 32 + (ar & 7) * 2 + (tid & 1)) * 4;
        const uint32_t avp = sb + SM_VP + (tid & 1) * (VPSTRIDE * 2) +
                             (ar < 32 ? 16 * ((ar & 3) >> 1) + (ar & 1) * 8 + (ar >> 2) : 32 + (ar & 1) * 8 + ((ar - 32) >> 1)) * 2;
        uint32_t af[4][4][4], ae[4][2][4], wf[4][3][4];
        if (typeA) {
#pragma unroll
            for (int i = 0; i < 4; i++) mbar_wait(BAR(B_MID + i), 0);
#pragma unroll
            for (int s = 0; s < 4; s++) { ldsm4t(ae[s][0], pe + s * 512); ldsm4t(ae[s][1], (pe ^ 16) + s * 512); ldsm4t(wf[s][2], aeb + s * 32); }
        }
        const uint4 mb = lds128(sb + SM_MB + tid * 16);
        mbar_wait(BAR(B_F + warp), 0);
#pragma unroll
        for (int s = 0; s < 4; s++)
#pragma unroll
            for (int j = 0; j < 4; j++) ldsm4t(af[s][j], (pb ^ (j << 4)) + s * 1024);
        TSL(40 + warp);
        uint32_t a[2], e[2];
        pollN<2>(&gs->x1[cta & 3][tid >> 2][(tid & 3) * 2], -((tid >> 2) * 16 + (tid & 3) * 2), tag, a, e);
        TSL(50 + warp);
        uint32_t mean2; float r0, r1;
        ln_stats(a[0], e[0], a[1], sb + SM_ST, warp, lane, mean2, r0, r1);
        const uint32_t ha = modulate2(a[0], mean2, r0, r1, mb.x, mb.y);
        const uint32_t hb = modulate2(e[0], mean2, r0, r1, mb.z, mb.w);
        sts32(sb + SM_HB + tid * 4, __byte_perm(ha, hb, 0x5410));
        sts32(sb + SM_HB + HSTRIDE * 2 + tid * 4, __byte_perm(ha, hb, 0x7632));
        __syncwarp();
        float acc[6][4];
#pragma unroll
        for (int j = 0; j < 6; j++) acc[j][0] = acc[j][1] = acc[j][2] = acc[j][3] = 0.f;
#pragma unroll
        for (int s = 0; s < 4; s++) {
            const uint32_t b0 = lds32(hbo + s * 32), b1 = lds32(hbo + s * 32 + 16);
#pragma unroll
            for (int j = 0; j < 4; j++) mma16816(acc[j], af[s][j][0], af[s][j][1], af[s][j][2], af[s][j][3], b0, b1);
            if (typeA) {
                mma16816(acc[4], ae[s][0][0], ae[s][0][1], ae[s][0][2], ae[s][0][3], b0, b1);
                mma16816(acc[5], ae[s][1][0], ae[s][1][1], ae[s][1][2], ae[s][1][3], b0, b1);
            }
        }
        if (c == 0) {
#pragma unroll
            for (int j = 0; j < 6; j++) { sts64f(redw + j * 128, acc[j][0], acc[j][1]); sts64f(redw + j * 128 + 64, acc[j][2], acc[j][3]); }
        }
        TS(15);
        csync();
        if (tid < (typeA ? 96 : 64)) {
            const uint32_t gu = pack_bf(red9(ared, 0), red9(ared, 16));
            const uint32_t sg = pack_bf(silu_f(bf_lo(gu)), 0.f);
            const uint32_t hh = hmul2(sg, gu >> 16);
            asm volatile("st.shared.b16 [%0], %1;" ::"r"(avp), "h"((unsigned short)hh) : "memory");
        }
#pragma unroll
        for (int i = 0; i < 4; i++) mbar_wait(BAR(B_W2 + i), 0);
#pragma unroll
        for (int i = 0; i < 4; i++) { ldsm4t(wf[i][0], ab + i * 32); ldsm4t(wf[i][1], ab + i * 32 + 2 * ROWB); }
        csync();
        TS(18);
        uint32_t b0[3], b1[3];
#pragma unroll
        for (int k = 0; k < 3; k++) { b0[k] = lds32(vpb + k * 32); b1[k] = lds32(vpb + k * 32 + 16); }
        float o[4][4];
#pragma unroll
        for (int i = 0; i < 4; i++) { o[i][0] = o[i][1] = o[i][2] = o[i][3] = 0.f; mma16816(o[i], wf[i][0][0], wf[i][0][1], wf[i][0][2], wf[i][0][3], b0[0], b1[0]); }
#pragma unroll
        for (int i = 0; i < 4; i++) mma16816(o[i], wf[i][1][0], wf[i][1][1], wf[i][1][2], wf[i][1][3], b0[1], b1[1]);
        if (typeA) {
#pragma unroll
            for (int i = 0; i < 4; i++) mma16816(o[i], wf[i][2][0], wf[i][2][1], wf[i][2][2], wf[i][2][3], b0[2], b1[2]);
        }
        publish4(o, c, dst, tag);
    }
    TS(19);
    if (reducer && warp < 8) {
        uint32_t a[4], e[4];
        pollN<4>(&gs->p4[warp * 16 + (lane >> 3)][cta * 8 + (lane & 7)][0], 4 * D_ * 2, tag, a, e);
        float v0 = (__uint_as_float(a[0]) + __uint_as_float(a[1])) + (__uint_as_float(a[2]) + __uint_as_float(a[3]));
        float v1 = (__uint_as_float(e[0]) + __uint_as_float(e[1])) + (__uint_as_float(e[2]) + __uint_as_float(e[3]));
        v0 += __shfl_xor_sync(0xffffffffu, v0, 8); v1 += __shfl_xor_sync(0xffffffffu, v1, 8);
        v0 += __shfl_xor_sync(0xffffffffu, v0, 16); v1 += __shfl_xor_sync(0xffffffffu, v1, 16);
        if (lane < 8) sts64f(sb + SM_SP + warp * 64 + lane * 8, v0, v1);
        if (warp == 0) {
            async8();
            uint32_t r[2];
            sum8(r);
            const uint32_t y0 = hadd2(x1v[0], hmul2(gbv[0], r[0])), y1 = hadd2(x1v[1], hmul2(gbv[1], r[1]));
            uint32_t* o32 = reinterpret_cast<uint32_t*>(out);
            if (lane < 8) o32[(lane >> 2) * (D_ / 2) + (rcol >> 1)] = __byte_perm(y0, y1, (lane & 4) ? 0x7632 : 0x5410);
            if (cta == 0 && lane == 0) asm volatile("st.relaxed.gpu.global.u32 [%0], %1;" ::"l"(&gs->epoch), "r"(tag) : "memory");
            TS(20);
        } else {
            asm volatile("bar.arrive 2, 256;" ::: "memory");
        }
    }
}

typedef CUresult (*EncodeFn)(CUtensorMap*, CUtensorMapDataType, cuuint32_t, void*, const cuuint64_t*, const cuuint64_t*, const cuuint32_t*,
                             const cuuint32_t*, CUtensorMapInterleave, CUtensorMapSwizzle, CUtensorMapL2promotion, CUtensorMapFloatOOBfill);

void make_map(EncodeFn fn, CUtensorMap* m, const void* p, uint64_t cols, uint64_t rows, uint32_t bcols, uint32_t brows,
              CUtensorMapSwizzle sw, CUtensorMapL2promotion pr) {
    cuuint64_t dims[2] = {cols, rows};
    cuuint64_t strides[1] = {cols * 2};
    cuuint32_t box[2] = {bcols, brows};
    cuuint32_t es[2] = {1, 1};
    fn(m, CU_TENSOR_MAP_DATA_TYPE_BFLOAT16, 2, const_cast<void*>(p), dims, strides, box, es, CU_TENSOR_MAP_INTERLEAVE_NONE, sw, pr,
       CU_TENSOR_MAP_FLOAT_OOB_FILL_NONE);
}

}

extern "C" void kernel_launch(void* const* d_in, const int* in_sizes, int n_in, void* d_out, int out_size) {
    (void)in_sizes; (void)n_in; (void)out_size;
    static EncodeFn enc = nullptr;
    if (!enc) {
        void* fp = nullptr;
        cudaDriverEntryPointQueryResult qr;
        cudaGetDriverEntryPoint("cuTensorMapEncodeTiled", &fp, cudaEnableDefault, &qr);
        enc = (EncodeFn)fp;
        cudaFuncSetAttribute(fused_block_kernel, cudaFuncAttributeMaxDynamicSharedMemorySize, SM_TOTAL);
    }
    const __nv_bfloat16* x    = (const __nv_bfloat16*)d_in[0];
    const __nv_bfloat16* wo   = (const __nv_bfloat16*)d_in[4];
    const __nv_bfloat16* w2   = (const __nv_bfloat16*)d_in[8];
    const __nv_bfloat16* cvec = (const __nv_bfloat16*)d_in[9];
    CUtensorMap tk, tv, tq, tm, t1, t3, t1x, t3x;
    make_map(enc, &tk, d_in[1], DH, 2ull * HKV * SK, 64, TILE_KEYS, CU_TENSOR_MAP_SWIZZLE_128B, CU_TENSOR_MAP_L2_PROMOTION_L2_256B);
    make_map(enc, &tv, d_in[2], DH, 2ull * HKV * SK, 64, TILE_KEYS, CU_TENSOR_MAP_SWIZZLE_128B, CU_TENSOR_MAP_L2_PROMOTION_L2_256B);
    make_map(enc, &tq, d_in[3], NQ, D_, 32, 64, CU_TENSOR_MAP_SWIZZLE_64B, CU_TENSOR_MAP_L2_PROMOTION_L2_128B);
    make_map(enc, &tm, d_in[10], NMOD, D_, 32, 64, CU_TENSOR_MAP_SWIZZLE_64B, CU_TENSOR_MAP_L2_PROMOTION_L2_128B);
    make_map(enc, &t1, d_in[6], FF, D_, 32, 64, CU_TENSOR_MAP_SWIZZLE_64B, CU_TENSOR_MAP_L2_PROMOTION_L2_128B);
    make_map(enc, &t3, d_in[7], FF, D_, 32, 64, CU_TENSOR_MAP_SWIZZLE_64B, CU_TENSOR_MAP_L2_PROMOTION_L2_128B);
    make_map(enc, &t1x, d_in[6], FF, D_, 16, 192, CU_TENSOR_MAP_SWIZZLE_32B, CU_TENSOR_MAP_L2_PROMOTION_L2_128B);
    make_map(enc, &t3x, d_in[7], FF, D_, 16, 192, CU_TENSOR_MAP_SWIZZLE_32B, CU_TENSOR_MAP_L2_PROMOTION_L2_128B);
    fused_block_kernel<<<NCTA, NTHREADS, SM_TOTAL>>>(tk, tv, tq, tm, t1, t3, t1x, t3x, x, wo, w2, cvec, (const __nv_bfloat16*)d_in[10], (__nv_bfloat16*)d_out);
}
```

```cpp
#include <cuda_runtime.h>
#include <cuda.h>
#include <cuda_bf16.h>
#include <stdint.h>

namespace {

constexpr int D_   = 576;
constexpr int HKV  = 16;
constexpr int SK   = 8192;
constexpr int DH   = 128;
constexpr int FF   = 4608;
constexpr int NQ   = 4096;
constexpr int NMOD = 6 * D_;

constexpr int NCTA     = 128;
constexpr int NCW      = 9;
constexpr int NCT      = NCW * 32;
constexpr int NTHREADS = NCT + 32;
constexpr int KEYS_PER_CTA = SK / 4;
constexpr int TILE_KEYS = 64;
constexpr int NTILES   = KEYS_PER_CTA / TILE_KEYS;
constexpr int NITEMS   = 2 * NTILES;
constexpr int TILE_BYTES = TILE_KEYS * DH * 2;
constexpr int NRING = 8;
constexpr int BOX_BYTES = 64 * 64;
constexpr int PLANE_BYTES = 9 * BOX_BYTES;
constexpr int ROWB = D_ * 2;

#define TUNE_DH 2
#define TUNE_DB 4
#define TUNE_DWO 3
#define TUNE_DW 2
#define TUNE_DW2 8
#define TUNE_SLEEP 1000
#define TUNE_RST 16
#define TUNE_JM2 3
#define TUNE_PRE 26

static_assert(TUNE_DH <= 8 && TUNE_DB <= 8 && TUNE_DWO <= 8 && TUNE_DW <= 8 && TUNE_DW2 <= 8, "a window may not reach a re-armed ring barrier");

constexpr int NM1CTA = 36;
constexpr int NMODCTA = NMOD / 32;
constexpr int NWO_CTA = 96;
constexpr int NRED_CTA = 72;

constexpr int SM_RING  = 0;
constexpr int SM_X     = NRING * TILE_BYTES;
constexpr int SM_XA    = SM_X;
constexpr int SM_XB    = SM_X + PLANE_BYTES;
constexpr int SM_XW2E  = SM_X + PLANE_BYTES;
constexpr int SM_W1B8  = 186880;
constexpr int SM_W3B8  = SM_W1B8 + BOX_BYTES;
constexpr int SM_W2G7  = SM_W3B8 + BOX_BYTES + 112;
constexpr int SM_MISC  = SM_X + 2 * PLANE_BYTES;
constexpr int SM_BAR   = SM_MISC;
constexpr int SM_SP    = SM_BAR + 320;
constexpr int HSTRIDE  = 584;
constexpr int SM_SC    = SM_SP + 8192;
constexpr int SM_HB    = SM_SC + 2 * HSTRIDE * 2;
constexpr int SM_RED   = SM_HB + 2 * HSTRIDE * 2;
constexpr int SM_MB    = SM_RED + 9 * 192 * 4;
constexpr int QSTRIDE  = 136;
constexpr int SM_QS    = SM_MB + D_ * 8;
constexpr int VPSTRIDE = 56;
constexpr int SM_VP    = SM_QS + 2 * QSTRIDE * 2;
constexpr int SM_ST    = SM_VP + 2 * VPSTRIDE * 2;
constexpr int SM_FAC   = SM_ST + 9 * 16;
constexpr int SM_HIST  = SM_FAC + 16;
constexpr int SM_TOTAL = SM_HIST + 64;
static_assert(SM_TOTAL <= 232448, "smem");
static_assert(SM_W2G7 + 4 * ROWB <= SM_MISC, "smem");
static_assert(SM_X + 8 * (6 * ROWB + 16) <= SM_W1B8, "smem");
static_assert((SM_ST % 16) == 0 && (SM_RED % 16) == 0 && (SM_MB % 16) == 0 && (SM_SP % 16) == 0, "align");

enum { B_KVFULL = 0, B_KVEMPTY = 8, B_WM = 16, B_WQ = 18, B_XFREE = 20, B_FAC = 21, B_MID = 22, B_W2 = 26, B_F = 30, B_OPEN = 39, B_COUNT = 40 };
constexpr int SM_W1 = SM_RING, SM_W3 = SM_RING + 32768, SM_W2 = SM_RING + 65536;

typedef unsigned long long u64;
struct __align__(128) Scratch {
    u64 h1[4][D_];
    u64 mod[2][D_][2];
    u64 q[2][NQ / 2];
    u64 ml[NCTA][16];
    u64 o[NCTA][2][8][8][2];
    uint4 p2[NWO_CTA][D_ / 2];
    u64 x1[4][NRED_CTA][16];
    uint4 p4[NCTA][D_ / 2];
    unsigned int epoch;
};
__device__ Scratch g_s;

#define TS(i)
#define TSL(i)

__device__ __forceinline__ uint32_t smem_u32(const void* p) { return (uint32_t)__cvta_generic_to_shared(p); }
__device__ __forceinline__ uint32_t pack_bf(float lo, float hi) {
    uint32_t r; asm("cvt.rn.bf16x2.f32 %0, %1, %2;" : "=r"(r) : "f"(hi), "f"(lo)); return r;
}
__device__ __forceinline__ float bf_lo(uint32_t v) { return __uint_as_float(v << 16); }
__device__ __forceinline__ float bf_hi(uint32_t v) { return __uint_as_float(v & 0xffff0000u); }
__device__ __forceinline__ uint32_t hsub2(uint32_t a, uint32_t b) { uint32_t r; asm("sub.rn.bf16x2 %0, %1, %2;" : "=r"(r) : "r"(a), "r"(b)); return r; }
__device__ __forceinline__ uint32_t hadd2(uint32_t a, uint32_t b) { uint32_t r; asm("add.rn.bf16x2 %0, %1, %2;" : "=r"(r) : "r"(a), "r"(b)); return r; }
__device__ __forceinline__ uint32_t hmul2(uint32_t a, uint32_t b) { uint32_t r; asm("mul.rn.bf16x2 %0, %1, %2;" : "=r"(r) : "r"(a), "r"(b)); return r; }
__device__ __forceinline__ float ex2(float x) { float r; asm("ex2.approx.ftz.f32 %0, %1;" : "=f"(r) : "f"(x)); return r; }
__device__ __forceinline__ float rcp(float x) { float r; asm("rcp.approx.ftz.f32 %0, %1;" : "=f"(r) : "f"(x)); return r; }
constexpr float LOG2E = 1.4426950408889634f;
__device__ __forceinline__ float silu_f(float x) { return x * rcp(1.0f + ex2(-x * LOG2E)); }

__device__ __forceinline__ void mbar_init(uint32_t bar, int cnt) { asm volatile("mbarrier.init.shared::cta.b64 [%0], %1;" ::"r"(bar), "r"(cnt)); }
__device__ __forceinline__ void mbar_expect_tx(uint32_t bar, uint32_t bytes) { asm volatile("mbarrier.arrive.expect_tx.shared::cta.b64 _, [%0], %1;" ::"r"(bar), "r"(bytes) : "memory"); }
__device__ __forceinline__ void mbar_arrive(uint32_t bar) { asm volatile("mbarrier.arrive.shared::cta.b64 _, [%0];" ::"r"(bar) : "memory"); }
__device__ __forceinline__ bool mbar_try(uint32_t bar, uint32_t parity) {
    uint32_t ok;
    asm volatile("{\n.reg .pred p;\nmbarrier.try_wait.parity.shared::cta.b64 p, [%1], %2;\nselp.u32 %0, 1, 0, p;\n}\n" : "=r"(ok) : "r"(bar), "r"(parity) : "memory");
    return ok != 0;
}
__device__ __forceinline__ bool mbar_test(uint32_t bar, uint32_t parity) {
    uint32_t ok;
    asm volatile("{\n.reg .pred p;\nmbarrier.test_wait.parity.shared::cta.b64 p, [%1], %2;\nselp.u32 %0, 1, 0, p;\n}\n" : "=r"(ok) : "r"(bar), "r"(parity) : "memory");
    return ok != 0;
}
__device__ __forceinline__ void mbar_wait(uint32_t bar, uint32_t parity) {
    uint32_t spins = 0;
    while (!mbar_try(bar, parity)) { if (++spins > (1u << 22)) __trap(); }
}
__device__ __forceinline__ void bulk_g2s(uint32_t dst, const void* src, uint32_t bytes, uint32_t bar, uint64_t pol) {
    asm volatile("cp.async.bulk.shared::cluster.global.mbarrier::complete_tx::bytes.L2::cache_hint [%0], [%1], %2, [%3], %4;" ::"r"(dst), "l"(src), "r"(bytes), "r"(bar), "l"(pol) : "memory");
}
__device__ __forceinline__ void tma2d(uint32_t dst, const CUtensorMap* map, int c0, int c1, uint32_t bar, uint64_t pol) {
    asm volatile("cp.async.bulk.tensor.2d.shared::cluster.global.mbarrier::complete_tx::bytes.L2::cache_hint [%0], [%1, {%2, %3}], [%4], %5;"
                 ::"r"(dst), "l"(map), "r"(c0), "r"(c1), "r"(bar), "l"(pol) : "memory");
}
__device__ __forceinline__ void cp16(uint32_t dst, const void* src) { asm volatile("cp.async.cg.shared.global [%0], [%1], 16;" ::"r"(dst), "l"(src) : "memory"); }
__device__ __forceinline__ void csync() { asm volatile("bar.sync 1, 288;" ::: "memory"); }
__device__ __forceinline__ void async8() { asm volatile("bar.sync 2, 256;" ::: "memory"); }

__device__ __forceinline__ void ldsm4(uint32_t (&r)[4], uint32_t addr) {
    asm volatile("ldmatrix.sync.aligned.m8n8.x4.shared.b16 {%0,%1,%2,%3}, [%4];" : "=r"(r[0]), "=r"(r[1]), "=r"(r[2]), "=r"(r[3]) : "r"(addr) : "memory");
}
__device__ __forceinline__ void ldsm4t(uint32_t (&r)[4], uint32_t addr) {
    asm volatile("ldmatrix.sync.aligned.m8n8.x4.trans.shared.b16 {%0,%1,%2,%3}, [%4];" : "=r"(r[0]), "=r"(r[1]), "=r"(r[2]), "=r"(r[3]) : "r"(addr) : "memory");
}
__device__ __forceinline__ void mma16816(float (&d)[4], uint32_t a0, uint32_t a1, uint32_t a2, uint32_t a3, uint32_t b0, uint32_t b1) {
    asm("mma.sync.aligned.m16n8k16.row.col.f32.bf16.bf16.f32 {%0,%1,%2,%3}, {%4,%5,%6,%7}, {%8,%9}, {%0,%1,%2,%3};"
                 : "+f"(d[0]), "+f"(d[1]), "+f"(d[2]), "+f"(d[3]) : "r"(a0), "r"(a1), "r"(a2), "r"(a3), "r"(b0), "r"(b1));
}
__device__ __forceinline__ uint32_t ldg32(const uint32_t* p) { uint32_t v; asm volatile("ld.global.nc.u32 %0, [%1];" : "=r"(v) : "l"(p)); return v; }
__device__ __forceinline__ uint32_t lds32(uint32_t addr) { uint32_t v; asm volatile("ld.shared.u32 %0, [%1];" : "=r"(v) : "r"(addr) : "memory"); return v; }
__device__ __forceinline__ float ldsf(uint32_t addr) { float v; asm volatile("ld.shared.f32 %0, [%1];" : "=f"(v) : "r"(addr) : "memory"); return v; }
__device__ __forceinline__ uint4 lds128(uint32_t addr) { uint4 v; asm volatile("ld.shared.v4.u32 {%0,%1,%2,%3}, [%4];" : "=r"(v.x), "=r"(v.y), "=r"(v.z), "=r"(v.w) : "r"(addr) : "memory"); return v; }
__device__ __forceinline__ void sts32(uint32_t addr, uint32_t v) { asm volatile("st.shared.u32 [%0], %1;" ::"r"(addr), "r"(v) : "memory"); }
__device__ __forceinline__ void sts64(uint32_t addr, uint32_t a, uint32_t b) { asm volatile("st.shared.v2.u32 [%0], {%1,%2};" ::"r"(addr), "r"(a), "r"(b) : "memory"); }
__device__ __forceinline__ void sts64f(uint32_t addr, float a, float b) { asm volatile("st.shared.v2.f32 [%0], {%1,%2};" ::"r"(addr), "f"(a), "f"(b) : "memory"); }
__device__ __forceinline__ void sts128(uint32_t addr, uint4 v) { asm volatile("st.shared.v4.u32 [%0], {%1,%2,%3,%4};" ::"r"(addr), "r"(v.x), "r"(v.y), "r"(v.z), "r"(v.w) : "memory"); }

__device__ __forceinline__ void st_pkt(u64* p, uint32_t v, uint32_t tag) {
    asm volatile("{\n.reg .b64 t;\nmov.b64 t, {%1,%2};\nst.relaxed.gpu.global.b64 [%0], t;\n}\n" ::"l"(p), "r"(v), "r"(tag) : "memory");
}
__device__ __forceinline__ void st_pkt2(u64* p, uint32_t a, uint32_t b, uint32_t tag) {
    asm volatile("{\n.reg .b64 t,u;\nmov.b64 t, {%1,%3};\nmov.b64 u, {%2,%3};\nst.relaxed.gpu.global.v2.b64 [%0], {t,u};\n}\n" ::"l"(p), "r"(a), "r"(b), "r"(tag) : "memory");
}
template <int OFF>
__device__ __forceinline__ void st_pkt2_if(bool p, const u64* base, float a, float b, uint32_t tag) {
    asm volatile("{\n.reg .pred p;\n.reg .b64 t,u;\nsetp.ne.u32 p, %4, 0;\nmov.b64 t, {%1,%3};\nmov.b64 u, {%2,%3};\n@p st.relaxed.gpu.global.v2.b64 [%0+%5], {t,u};\n}\n"
                 ::"l"(base), "r"(__float_as_uint(a)), "r"(__float_as_uint(b)), "r"(tag), "r"((uint32_t)p), "n"(OFF) : "memory");
}
__device__ __forceinline__ uint4 ld_pkt2(const u64* p) {
    uint4 v;
    asm volatile("{\n.reg .b64 t,u;\nld.relaxed.gpu.global.v2.b64 {t,u}, [%4];\nmov.b64 {%0,%1}, t;\nmov.b64 {%2,%3}, u;\n}\n"
                 : "=r"(v.x), "=r"(v.y), "=r"(v.z), "=r"(v.w) : "l"(p) : "memory");
    return v;
}
__device__ __forceinline__ void ld_pkt2_if(uint4& v, const u64* p, uint32_t tag) {
    asm volatile("{\n.reg .pred p,q;\n.reg .b64 t,u;\nsetp.ne.u32 q, %1, %5;\nsetp.ne.or.u32 p, %3, %5, q;\nmov.b64 t, {%0,%1};\nmov.b64 u, {%2,%3};\n"
                 "@p ld.relaxed.gpu.global.v2.b64 {t,u}, [%4];\nmov.b64 {%0,%1}, t;\nmov.b64 {%2,%3}, u;\n}\n"
                 : "+r"(v.x), "+r"(v.y), "+r"(v.z), "+r"(v.w) : "l"(p), "r"(tag) : "memory");
}
template <int N, int SLEEP = 0>
__device__ __forceinline__ void pollN(const u64* p, int stride, uint32_t tag, uint32_t (&a)[N], uint32_t (&b)[N]) {
    uint32_t spins = 0;
    uint4 v[N];
#pragma unroll
    for (int i = 0; i < N; i++) v[i] = ld_pkt2(p + (size_t)i * stride);
    while (true) {
        uint32_t bad = 0;
#pragma unroll
        for (int i = 0; i < N; i++) bad |= (v[i].y ^ tag) | (v[i].w ^ tag);
        if (!__any_sync(0xffffffffu, bad != 0)) break;
        if (SLEEP) __nanosleep(SLEEP);
        if (++spins > (1u << 22)) __trap();
#pragma unroll
        for (int i = 0; i < N; i++) ld_pkt2_if(v[i], p + (size_t)i * stride, tag);
    }
#pragma unroll
    for (int i = 0; i < N; i++) { a[i] = v[i].x; b[i] = v[i].z; }
}
__device__ __forceinline__ void st_w4(const uint4* p, uint32_t a, uint32_t b, uint32_t c, uint32_t d) {
    asm volatile("st.relaxed.gpu.global.v4.b32 [%0], {%1,%2,%3,%4};" ::"l"(p), "r"(a), "r"(b), "r"(c), "r"(d) : "memory");
}
__device__ __forceinline__ void ld_w4_if(uint4& v, const uint4* p, bool pred) {
    asm volatile("{\n.reg .pred p;\nsetp.ne.u32 p, %5, 0;\n@p ld.relaxed.gpu.global.v4.b32 {%0,%1,%2,%3}, [%4];\n}\n"
                 : "+r"(v.x), "+r"(v.y), "+r"(v.z), "+r"(v.w) : "l"(p), "r"((uint32_t)pred) : "memory");
}
__device__ __forceinline__ void gather_sum(const uint4* p, bool active, uint32_t t2, uint32_t dst, int lane) {
    uint4 v0 = make_uint4(0, 0, 0, 0), v1 = v0;
    bool m0 = active, m1 = active;
    uint32_t spins = 0;
    while (true) {
        ld_w4_if(v0, p, m0);
        ld_w4_if(v1, p + 8 * (D_ / 2), m1);
        m0 = m0 && ((((v0.x ^ t2) | (v0.y ^ t2) | (v0.z ^ t2) | (v0.w ^ t2)) & 3u) != 0);
        m1 = m1 && ((((v1.x ^ t2) | (v1.y ^ t2) | (v1.z ^ t2) | (v1.w ^ t2)) & 3u) != 0);
        if (!__any_sync(0xffffffffu, m0 || m1)) break;
        if (++spins > (1u << 22)) __trap();
    }
    float f[4] = {__uint_as_float(v0.x) + __uint_as_float(v1.x), __uint_as_float(v0.y) + __uint_as_float(v1.y),
                  __uint_as_float(v0.z) + __uint_as_float(v1.z), __uint_as_float(v0.w) + __uint_as_float(v1.w)};
#pragma unroll
    for (int o = 4; o < 32; o <<= 1)
#pragma unroll
        for (int k = 0; k < 4; k++) f[k] += __shfl_xor_sync(0xffffffffu, f[k], o);
    if (lane < 4) { sts64f(dst + lane * 8, f[0], f[1]); sts64f(dst + 32 + lane * 8, f[2], f[3]); }
}
__device__ __forceinline__ void publish4(const float (&a)[4][4], int c, const uint4* dst, uint32_t t2) {
    uint32_t v[4];
#pragma unroll
    for (int k = 0; k < 4; k++) {
        const float lo = (c & 1) ? a[1][k] : a[0][k], hi = (c & 1) ? a[3][k] : a[2][k];
        v[k] = (__float_as_uint((c & 2) ? hi : lo) & ~3u) | t2;
    }
    st_w4(dst, v[0], v[1], v[2], v[3]);
}

__device__ __noinline__ void plane_gemv(uint32_t plane, uint32_t vec, uint32_t red, int warp, int lane) {
    const int g = lane >> 2, c = lane & 3, mi = lane >> 3, kap = lane & 7;
    const int rowl = kap + 8 * (mi >> 1);
    const uint32_t a0 = plane + warp * BOX_BYTES + rowl * 64 + ((((mi & 1)) ^ ((rowl >> 1) & 3)) << 4);
    const uint32_t bo = vec + (g & 1) * (HSTRIDE * 2) + warp * 128 + c * 4;
    float acc0[4] = {0.f, 0.f, 0.f, 0.f}, acc1[4] = {0.f, 0.f, 0.f, 0.f};
#pragma unroll
    for (int s = 0; s < 4; s++) {
        uint32_t x[4], y[4];
        ldsm4t(x, a0 + s * 1024);
        ldsm4t(y, (a0 ^ 32) + s * 1024);
        const uint32_t b0 = lds32(bo + s * 32), b1 = lds32(bo + s * 32 + 16);
        mma16816(acc0, x[0], x[1], x[2], x[3], b0, b1);
        mma16816(acc1, y[0], y[1], y[2], y[3], b0, b1);
    }
    if (c == 0) {
        const uint32_t r = red + warp * 768 + g * 8;
        sts64f(r, acc0[0], acc0[1]); sts64f(r + 64, acc0[2], acc0[3]);
        sts64f(r + 128, acc1[0], acc1[1]); sts64f(r + 192, acc1[2], acc1[3]);
    }
}
__device__ __forceinline__ float red9(uint32_t red, int idx) {
    float v[9];
#pragma unroll
    for (int w = 0; w < 9; w++) v[w] = ldsf(red + w * 768 + idx * 4);
    return ((v[0] + v[1]) + (v[2] + v[3])) + ((v[4] + v[5]) + (v[6] + v[7])) + v[8];
}

__device__ __forceinline__ void ln_stats(uint32_t xa, uint32_t xb, uint32_t sh, uint32_t st, int warp, int lane, uint32_t& mean2, float& r0, float& r1) {
    const float s0 = bf_lo(sh), s1 = bf_hi(sh);
    const float a0 = bf_lo(xa) - s0, a1 = bf_hi(xa) - s1, b0 = bf_lo(xb) - s0, b1 = bf_hi(xb) - s1;
    float u0 = a0 + b0, u1 = a1 + b1, q0 = a0 * a0 + b0 * b0, q1 = a1 * a1 + b1 * b1;
#pragma unroll
    for (int o = 16; o > 0; o >>= 1) {
        u0 += __shfl_xor_sync(0xffffffffu, u0, o); u1 += __shfl_xor_sync(0xffffffffu, u1, o);
        q0 += __shfl_xor_sync(0xffffffffu, q0, o); q1 += __shfl_xor_sync(0xffffffffu, q1, o);
    }
    if (lane == 0) sts128(st + warp * 16, make_uint4(__float_as_uint(u0), __float_as_uint(u1), __float_as_uint(q0), __float_as_uint(q1)));
    csync();
    uint4 v[9];
#pragma unroll
    for (int w = 0; w < 9; w++) v[w] = lds128(st + w * 16);
#define SUM9(f) ((((__uint_as_float(v[0].f) + __uint_as_float(v[1].f)) + (__uint_as_float(v[2].f) + __uint_as_float(v[3].f))) + \
                  ((__uint_as_float(v[4].f) + __uint_as_float(v[5].f)) + (__uint_as_float(v[6].f) + __uint_as_float(v[7].f)))) + __uint_as_float(v[8].f))
    u0 = SUM9(x) * (1.0f / D_); u1 = SUM9(y) * (1.0f / D_);
    q0 = SUM9(z); q1 = SUM9(w);
#undef SUM9
    const uint32_t var2 = pack_bf(fmaxf(fmaf(q0, 1.0f / D_, -u0 * u0), 0.f), fmaxf(fmaf(q1, 1.0f / D_, -u1 * u1), 0.f));
    mean2 = pack_bf(u0 + s0, u1 + s1);
    const uint32_t ve2 = pack_bf(bf_lo(var2) + 1e-5f, bf_hi(var2) + 1e-5f);
    float d0, d1;
    asm("sqrt.approx.ftz.f32 %0, %1;" : "=f"(d0) : "f"(bf_lo(ve2)));
    asm("sqrt.approx.ftz.f32 %0, %1;" : "=f"(d1) : "f"(bf_hi(ve2)));
    const uint32_t sd2 = pack_bf(d0, d1);
    r0 = rcp(bf_lo(sd2)); r1 = rcp(bf_hi(sd2));
}
__device__ __forceinline__ uint32_t modulate2(uint32_t x, uint32_t mean2, float r0, float r1, uint32_t shift, uint32_t onepscale) {
    const uint32_t d = hsub2(x, mean2);
    const uint32_t y = pack_bf(bf_lo(d) * r0, bf_hi(d) * r1);
    return hadd2(hmul2(y, onepscale), shift);
}
constexpr uint32_t ONE2 = 0x3f803f80u;

__global__ void __launch_bounds__(NTHREADS, 1)
fused_block_kernel(const __grid_constant__ CUtensorMap tm_k, const __grid_constant__ CUtensorMap tm_v,
                   const __grid_constant__ CUtensorMap tm_wq, const __grid_constant__ CUtensorMap tm_wm,
                   const __grid_constant__ CUtensorMap tm_w1, const __grid_constant__ CUtensorMap tm_w3,
                   const __grid_constant__ CUtensorMap tm_w1x, const __grid_constant__ CUtensorMap tm_w3x,
                   const __nv_bfloat16* __restrict__ x, const __nv_bfloat16* __restrict__ wo, const __nv_bfloat16* __restrict__ w2,
                   const __nv_bfloat16* __restrict__ cvec, const __nv_bfloat16* __restrict__ wmod, __nv_bfloat16* __restrict__ out) {
    extern __shared__ __align__(1024) uint8_t smem[];
    int tid, cta;
    uint32_t sb;
    Scratch* gs;
    asm volatile("mov.u32 %0, %1;" : "=r"(tid) : "r"(threadIdx.x));
    asm volatile("mov.u32 %0, %1;" : "=r"(cta) : "r"(blockIdx.x));
    asm volatile("mov.u32 %0, %1;" : "=r"(sb) : "r"(smem_u32(smem)));
    asm volatile("mov.u64 %0, %1;" : "=l"(gs) : "l"(&g_s));
    const int warp = tid >> 5, lane = tid & 31;
    auto BAR = [&](int i) { return sb + SM_BAR + 8 * i; };

    const int bb = cta >> 6, kvh = (cta >> 2) & 15;
    const bool typeA = cta < 32;
    const int wj = cta - 32;
    const int nO = typeA ? 0 : (wj < 32 ? 2 : 3);
    const int o_r0 = wj < 32 ? 32 * wj : 1024 + 48 * (wj - 32);
    const bool m1 = cta < NM1CTA, m2 = cta >= NM1CTA && cta < NMODCTA;

    TS(0);
    const int krow0 = cta * KEYS_PER_CTA;
    const uint32_t* x32 = reinterpret_cast<const uint32_t*>(x);
    uint64_t pol;
    asm volatile("createpolicy.fractional.L2::evict_first.b64 %0, 1.0;" : "=l"(pol));
    if (tid == NCT) {
        mbar_init(BAR(B_WQ), 1); mbar_init(BAR(B_WQ + 1), 1); mbar_init(BAR(B_KVFULL), 1);
        asm volatile("fence.mbarrier_init.release.cluster;" ::: "memory");
        TSL(22);
        mbar_expect_tx(BAR(B_WQ), 5 * BOX_BYTES);
#pragma unroll
        for (int i = 0; i < 5; i++) tma2d(sb + SM_XB + (i < 4 ? i : 8) * BOX_BYTES, &tm_wq, cta * 32, (i < 4 ? i : 8) * 64, BAR(B_WQ), pol);
        mbar_expect_tx(BAR(B_WQ + 1), 4 * BOX_BYTES);
#pragma unroll
        for (int i = 4; i < 8; i++) tma2d(sb + SM_XB + i * BOX_BYTES, &tm_wq, cta * 32, i * 64, BAR(B_WQ + 1), pol);
        mbar_expect_tx(BAR(B_KVFULL), TILE_BYTES);
        tma2d(sb + SM_RING, &tm_k, 0, krow0, BAR(B_KVFULL), pol);
        tma2d(sb + SM_RING + 8192, &tm_k, 64, krow0, BAR(B_KVFULL), pol);
#pragma unroll
        for (int i = 1; i < 8; i++) mbar_init(BAR(B_KVFULL + i), 1);
#pragma unroll
        for (int i = 0; i < 8; i++) mbar_init(BAR(B_KVEMPTY + i), 8);
        mbar_init(BAR(B_WM), 1); mbar_init(BAR(B_WM + 1), 1);
#pragma unroll
        for (int i = B_FAC; i < B_COUNT; i++) mbar_init(BAR(i), 1);
        mbar_init(BAR(B_XFREE), NCW);
        asm volatile("fence.mbarrier_init.release.cluster;" ::: "memory");
    }
    uint32_t tag, c0 = 0, c1 = 0, u0 = 0, u1 = 0, z0 = 0, z1 = 0, xo0 = 0, xo1 = 0;
    asm volatile("ld.relaxed.gpu.global.u32 %0, [%1];" : "=r"(tag) : "l"(&gs->epoch) : "memory");
    if (cta < NMODCTA && warp < NCW) {
        const uint32_t* c32 = reinterpret_cast<const uint32_t*>(cvec);
        c0 = ldg32(c32 + tid); c1 = ldg32(c32 + D_ / 2 + tid);
        if (m1) {
            u0 = ldg32(x32 + tid); u1 = ldg32(x32 + D_ / 2 + tid);
            z0 = ldg32(x32); z1 = ldg32(x32 + D_ / 2);
            xo0 = ldg32(x32 + cta * 8 + (lane >> 2)); xo1 = ldg32(x32 + D_ / 2 + cta * 8 + (lane >> 2));
            const int g = lane >> 2, c = lane & 3;
            const char* src = reinterpret_cast<const char*>(wmod) + (size_t)(warp * 64 + g) * (NMOD * 2) + (c & 1) * (D_ * 2) + cta * 32 + (c >> 1) * 16;
            const uint32_t dst = sb + SM_XA + (warp * 64 + g) * 64 + ((c ^ ((g >> 1) & 3)) << 4);
#pragma unroll
            for (int i = 0; i < 8; i++) cp16(dst + i * 512, src + (size_t)i * 8 * (NMOD * 2));
        }
    }
    if (warp == NCW) {
        __syncwarp();
        asm volatile("bar.arrive 0, 320;" ::: "memory");
        if (lane != 0) return;
        const uint32_t hist = sb + SM_HIST;
        sts32(hist, BAR(B_WQ)); sts32(hist + 4, BAR(B_WQ + 1)); sts32(hist + 8, BAR(B_KVFULL));
        int n = 3;
        auto window = [&](int D) {
            if (n >= D) { const uint32_t h = lds32(hist + ((n - D) & 15) * 4); mbar_wait(h & ~1u, h & 1u); }
        };
        auto issued = [&](uint32_t bar, uint32_t par) { sts32(hist + (n & 15) * 4, bar | par); n++; };
        auto plane_half = [&](const CUtensorMap* map, uint32_t base, uint32_t box8, int bar, int half, int D) {
            window(D);
            mbar_expect_tx(BAR(bar + half), (half ? 4 : 5) * BOX_BYTES);
#pragma unroll
            for (int i = 0; i < 4; i++) tma2d(base + (half * 4 + i) * BOX_BYTES, map, cta * 32, (half * 4 + i) * 64, BAR(bar + half), pol);
            if (!half) tma2d(box8, map, cta * 32, 512, BAR(bar), pol);
            issued(BAR(bar + half), 0);
        };
        auto rows8 = [&](const __nv_bfloat16* w, int row0, int rpg, uint32_t base, uint32_t g7, uint32_t bar, int g0, int ng) {
            const uint32_t gb = rpg * ROWB;
#pragma unroll 1
            for (int gi = g0; gi < g0 + ng; gi++)
                bulk_g2s(gi < 7 ? base + gi * (gb + 16) : g7, reinterpret_cast<const char*>(w) + (size_t)row0 * ROWB + (size_t)gi * gb, gb, bar, pol);
        };
#pragma unroll 1
        for (int j = 1; j < NITEMS; j++) {
            const int s = j & 7;
            int D = TUNE_DB;
            if (j >= 8) mbar_wait(BAR(B_KVEMPTY + s), ((j >> 3) - 1) & 1);
            else if (!mbar_test(BAR(B_KVEMPTY), 0)) D = TUNE_DH;
            window(D);
            mbar_expect_tx(BAR(B_KVFULL + s), TILE_BYTES);
            const CUtensorMap* map = j < NTILES ? &tm_k : &tm_v;
            tma2d(sb + SM_RING + s * TILE_BYTES, map, 0, krow0 + (j & 31) * TILE_KEYS, BAR(B_KVFULL + s), pol);
            tma2d(sb + SM_RING + s * TILE_BYTES + 8192, map, 64, krow0 + (j & 31) * TILE_KEYS, BAR(B_KVFULL + s), pol);
            issued(BAR(B_KVFULL + s), (j >> 3) & 1);
            if (m2 && (j == TUNE_JM2 || j == TUNE_JM2 + 1)) plane_half(&tm_wm, sb + SM_XA, sb + SM_XA + 8 * BOX_BYTES, B_WM, j - TUNE_JM2, D);
        }
        TSL(16);
        mbar_wait(BAR(B_XFREE), 0);
        if (!typeA) {
#pragma unroll 1
            for (int h = 0; h < 4; h++) {
                window(TUNE_DWO);
                mbar_expect_tx(BAR(B_MID + h), 4 * nO * ROWB);
                rows8(wo, o_r0, 2 * nO, sb + SM_X, sb + SM_X + 7 * (2 * nO * ROWB + 16), BAR(B_MID + h), 2 * h, 2);
                issued(BAR(B_MID + h), 0);
            }
        }
        bool open = false;
        uint32_t spins = 0;
        auto tail_window = [&]() {
            while (!open) {
                const uint32_t h = lds32(hist + ((n - TUNE_DW) & 15) * 4);
                if (mbar_test(h & ~1u, h & 1u)) return;
                open = mbar_test(BAR(B_OPEN), 0);
                if (++spins > (1u << 27)) __trap();
            }
            window(TUNE_DW2);
        };
#pragma unroll 1
        for (int i = 0; i < 9; i++) {
            const int bx = i == 0 ? 8 : i - 1;
            if (i == 1) { mbar_wait(BAR(B_KVEMPTY + 0), 1); mbar_wait(BAR(B_KVEMPTY + 2), 1); }
            if (i == 5) { mbar_wait(BAR(B_KVEMPTY + 1), 1); mbar_wait(BAR(B_KVEMPTY + 3), 1); }
            tail_window();
            mbar_expect_tx(BAR(B_F + bx), 2 * BOX_BYTES);
            tma2d(sb + (i ? SM_W1 + bx * BOX_BYTES : SM_W1B8), &tm_w1, cta * 32, bx * 64, BAR(B_F + bx), pol);
            tma2d(sb + (i ? SM_W3 + bx * BOX_BYTES : SM_W3B8), &tm_w3, cta * 32, bx * 64, BAR(B_F + bx), pol);
            issued(BAR(B_F + bx), 0);
            if (typeA && i < 4) {
                tail_window();
                mbar_expect_tx(BAR(B_MID + i), i < 3 ? 2 * 6144 : 16 * ROWB);
                if (i < 3) {
                    tma2d(sb + SM_XA + i * 6144, &tm_w1x, NQ + 16 * cta, i * 192, BAR(B_MID + i), pol);
                    tma2d(sb + SM_XA + 18432 + i * 6144, &tm_w3x, NQ + 16 * cta, i * 192, BAR(B_MID + i), pol);
                } else rows8(w2, NQ + 16 * cta, 2, sb + SM_XW2E, sb + SM_XW2E + 7 * (2 * ROWB + 16), BAR(B_MID + 3), 0, 8);
                issued(BAR(B_MID + i), 0);
            }
        }
        mbar_wait(BAR(B_KVEMPTY + 4), 1);
        mbar_wait(BAR(B_KVEMPTY + 5), 1);
#pragma unroll 1
        for (int h = 0; h < 4; h++) {
            tail_window();
            mbar_expect_tx(BAR(B_W2 + h), 8 * ROWB);
            rows8(w2, cta * 32, 4, sb + SM_W2, sb + SM_W2G7, BAR(B_W2 + h), 2 * h, 2);
            issued(BAR(B_W2 + h), 0);
        }
        TSL(17);
        return;
    }

    const int g = lane >> 2, c = lane & 3, mi = lane >> 3, kap = lane & 7;
    const int whalf = (warp >> 2) & 1;
    const int rowl = kap + 8 * (mi >> 1);
    const uint32_t sw64 = (rowl >> 1) & 3;
    const uint32_t hbo = sb + SM_HB + (g & 1) * (HSTRIDE * 2) + warp * 128 + c * 4;
    const uint32_t redw = sb + SM_RED + warp * 768 + g * 8;
    if (warp == 0) {
        st_pkt(&gs->q[lane >> 4][cta * 16 + (lane & 15)], 0u, 0u);
        if (m1) st_pkt2(&gs->h1[lane >> 3][cta * 16 + (lane & 7) * 2], 0u, 0u, 0u);
    }
    if (cta < NMODCTA) {
        sts32(sb + SM_SC + tid * 4, pack_bf(silu_f(bf_lo(c0)), silu_f(bf_hi(c0))));
        sts32(sb + SM_SC + HSTRIDE * 2 + tid * 4, pack_bf(silu_f(bf_lo(c1)), silu_f(bf_hi(c1))));
        if (m1) {
            uint32_t mean2; float r0, r1;
            ln_stats(__byte_perm(u0, u1, 0x5410), __byte_perm(u0, u1, 0x7632), __byte_perm(z0, z1, 0x5410), sb + SM_ST, warp, lane, mean2, r0, r1);
            asm volatile("cp.async.wait_all;" ::: "memory");
            __syncwarp();
            TSL(70 + warp);
            plane_gemv(sb + SM_XA, sb + SM_SC, sb + SM_RED, warp, lane);
            csync();
            if (warp == 0) {
                const int idx = (lane >> 4) * 32 + (lane & 15);
                const float sa = red9(sb + SM_RED, idx), ca = red9(sb + SM_RED, idx + 16);
                const uint32_t sa2 = pack_bf(sa, __shfl_xor_sync(0xffffffffu, sa, 1)), ca2 = pack_bf(ca, __shfl_xor_sync(0xffffffffu, ca, 1));
                const uint32_t xo = __byte_perm(xo0, xo1, (lane & 2) ? 0x7632 : 0x5410);
                const uint32_t h = modulate2(xo, mean2, r0, r1, sa2, hadd2(ca2, ONE2));
                const uint32_t hp = __shfl_sync(0xffffffffu, h, (lane & 7) * 4), hq = __shfl_sync(0xffffffffu, h, (lane & 7) * 4 + 2);
                st_pkt2(&gs->h1[lane >> 3][cta * 16 + (lane & 7) * 2], hp, hq, tag + 1);
            }
            TS(2);
        }
    }
    tag += 1;
    asm volatile("bar.sync 0, 320;" ::: "memory");
    TS(1);
    {
        uint32_t af[4][2][4];
        const uint32_t a0 = sb + SM_XB + warp * BOX_BYTES + rowl * 64 + (((mi & 1) ^ sw64) << 4);
        mbar_wait(BAR(B_WQ + whalf), 0);
        TS(21);
#pragma unroll
        for (int s = 0; s < 4; s++) { ldsm4t(af[s][0], a0 + s * 1024); ldsm4t(af[s][1], (a0 ^ 32) + s * 1024); }
        uint32_t ha[1], hb[1];
        pollN<1>(&gs->h1[cta & 3][2 * tid], 0, tag, ha, hb);
        sts32(sb + SM_HB + tid * 4, __byte_perm(ha[0], hb[0], 0x5410));
        sts32(sb + SM_HB + HSTRIDE * 2 + tid * 4, __byte_perm(ha[0], hb[0], 0x7632));
        __syncwarp();
        TS(3);
        float acc0[4] = {0.f, 0.f, 0.f, 0.f}, acc1[4] = {0.f, 0.f, 0.f, 0.f};
#pragma unroll
        for (int s = 0; s < 4; s++) {
            const uint32_t b0 = lds32(hbo + s * 32), b1 = lds32(hbo + s * 32 + 16);
            mma16816(acc0, af[s][0][0], af[s][0][1], af[s][0][2], af[s][0][3], b0, b1);
            mma16816(acc1, af[s][1][0], af[s][1][1], af[s][1][2], af[s][1][3], b0, b1);
        }
        if (c == 0) {
            sts64f(redw, acc0[0], acc0[1]); sts64f(redw + 64, acc0[2], acc0[3]);
            sts64f(redw + 128, acc1[0], acc1[1]); sts64f(redw + 192, acc1[2], acc1[3]);
        }
        csync();
        if (warp == 0) {
            const int idx = (lane & 15) * 4 + (lane >> 4);
            st_pkt(&gs->q[lane >> 4][cta * 16 + (lane & 15)], pack_bf(red9(sb + SM_RED, idx), red9(sb + SM_RED, idx + 2)), tag);
        }
    }
    TS(4);
    auto mod2_phase = [&]() {
        if (m2) {
            mbar_wait(BAR(B_WM + whalf), 0);
            plane_gemv(sb + SM_XA, sb + SM_SC, sb + SM_RED, warp, lane);
            csync();
            if (tid < 64) {
                const float v = red9(sb + SM_RED, tid);
                const float o = __shfl_xor_sync(0xffffffffu, v, 1);
                const int which = cta / 18, i = (cta % 18) * 32 + (tid >> 1);
                if ((tid & 1) == 0) st_pkt(&gs->mod[(which == 2 || which == 5) ? 1 : 0][i][which >> 2], pack_bf(v, o), tag);
            }
        }
        asm volatile("fence.proxy.async.shared::cta;" ::: "memory");
        __syncwarp();
        if (lane == 0) mbar_arrive(BAR(B_XFREE));
    };

    const bool reducer = cta < NRED_CTA;
    const int rcol = (cta >> 1) * 16 + ((lane >> 1) & 1) * 8 + (cta & 1) * 4 + (lane & 1) * 2;
    const uint32_t t2 = tag % 3u + 1u;
    uint32_t gav[2] = {0, 0}, gbv[2] = {0, 0}, xin[2] = {0, 0};
    auto preload_tail = [&]() {
        if (reducer && warp == 0) {
            const uint32_t u0 = __ldg(x32 + (rcol >> 1)), u1 = __ldg(x32 + ((D_ + rcol) >> 1));
            xin[0] = __byte_perm(u0, u1, 0x5410); xin[1] = __byte_perm(u0, u1, 0x7632);
            pollN<2>(&gs->mod[1][rcol][0], 2, tag, gav, gbv);
        }
    };

    auto clear_own = [&]() {
        st_w4(&gs->p4[cta][warp * 32 + c * 8 + g], 0u, 0u, 0u, 0u);
        if (!typeA) st_w4(&gs->p2[wj][warp * 32 + c * 8 + g], 0u, 0u, 0u, 0u);
        if (warp < 8 && c < 2) st_pkt2(&gs->o[cta][c][warp][g][0], 0u, 0u, 0u);
    };
    if (warp == 8) {
        asm volatile("bar.sync 3, 64;" ::: "memory");
        mod2_phase();
#pragma unroll 1
        for (int i = lane; i < D_; i += 64) {
            uint32_t s2[2], c2[2];
            pollN<2, TUNE_SLEEP>(&gs->mod[0][i][0], 64, tag, s2, c2);
            sts64(sb + SM_MB + i * 8, s2[0], hadd2(c2[0], ONE2));
            sts64(sb + SM_MB + (i + 32) * 8, s2[1], hadd2(c2[1], ONE2));
        }
        {
            uint32_t a[1], e[1];
            pollN<1, TUNE_SLEEP>(&gs->ml[(cta & ~3) + ((lane >> 1) & 3)][(lane & 1) * 2], 0, tag, a, e);
            const float m = __uint_as_float(a[0]);
            float M = fmaxf(m, __shfl_xor_sync(0xffffffffu, m, 2));
            M = fmaxf(M, __shfl_xor_sync(0xffffffffu, M, 4));
            const float w = ex2((m - M) * LOG2E);
            float L = w * __uint_as_float(e[0]);
            L += __shfl_xor_sync(0xffffffffu, L, 2);
            L += __shfl_xor_sync(0xffffffffu, L, 4);
            if ((lane >> 1) == (cta & 3)) sts32(sb + SM_FAC + (lane & 1) * 4, __float_as_uint(w / L));
        }
        __syncwarp();
        if (lane == 0) mbar_arrive(BAR(B_FAC));
        clear_own();
        preload_tail();
    } else {
        if (tid < 64) {
            uint32_t a[1], e[1];
            pollN<1>(&gs->q[bb][kvh * 128 + tid * 2], 0, tag, a, e);
            sts64(sb + SM_QS + (tid >> 5) * (QSTRIDE * 2) + (tid & 31) * 8, a[0], e[0]);
        }
        async8();
        if (warp == 7) asm volatile("bar.arrive 3, 64;" ::: "memory");
        TS(5);
        uint32_t qa[8][2];
#pragma unroll
        for (int s = 0; s < 8; s++) {
            const uint32_t a = sb + SM_QS + (g & 1) * (QSTRIDE * 2) + (16 * s + 2 * c) * 2;
            qa[s][0] = lds32(a); qa[s][1] = lds32(a + 16);
        }
        constexpr float SCALE = 0.08838834764831845f;
        float mrun = -INFINITY;
        const uint32_t koff = (8 * warp + kap) * 128 + ((mi ^ kap) << 4);
        const uint32_t spw = sb + SM_SP + (g & 1) * 128 + c * 32;
#pragma unroll 1
        for (int t = 0; t < NTILES; t++) {
            const int s = t & 7;
            mbar_wait(BAR(B_KVFULL + s), (t >> 3) & 1);
            if ((t & 3) == 0) TS(24 + (t >> 2));
            float s0[4] = {0.f, 0.f, 0.f, 0.f}, s1[4] = {0.f, 0.f, 0.f, 0.f};
            const uint32_t ka = sb + SM_RING + s * TILE_BYTES + koff;
#pragma unroll
            for (int i = 0; i < 4; i++) {
                uint32_t u[4];
                ldsm4(u, (ka ^ ((i & 1) << 6)) + (i >> 1) * 8192);
                mma16816(s0, qa[2 * i][0], 0u, qa[2 * i][1], 0u, u[0], u[1]);
                mma16816(s1, qa[2 * i + 1][0], 0u, qa[2 * i + 1][1], 0u, u[2], u[3]);
            }
            __syncwarp();
            if (lane == 0) mbar_arrive(BAR(B_KVEMPTY + s));
            const uint32_t d0 = pack_bf(s0[0] + s1[0], s0[1] + s1[1]);
            const uint32_t e0 = pack_bf(bf_lo(d0) * SCALE, bf_hi(d0) * SCALE);
            mrun = fmaxf(mrun, fmaxf(bf_lo(e0), bf_hi(e0)));
            if (g < 2) sts32(spw + t * 256 + warp * 4, e0);
        }
        TS(6);
        mrun = fmaxf(mrun, __shfl_xor_sync(0xffffffffu, mrun, 1));
        mrun = fmaxf(mrun, __shfl_xor_sync(0xffffffffu, mrun, 2));
        if (lane == 0 || lane == 4) sts32(sb + SM_ST + (g * 8 + warp) * 4, __float_as_uint(mrun));
        async8();
        {
            const int h = (tid >> 2) & 1;
            const uint4 m0 = lds128(sb + SM_ST + h * 32), m1v = lds128(sb + SM_ST + h * 32 + 16);
            const float M = fmaxf(fmaxf(fmaxf(__uint_as_float(m0.x), __uint_as_float(m0.y)), fmaxf(__uint_as_float(m0.z), __uint_as_float(m0.w))),
                                  fmaxf(fmaxf(__uint_as_float(m1v.x), __uint_as_float(m1v.y)), fmaxf(__uint_as_float(m1v.z), __uint_as_float(m1v.w))));
            float l = 0.f;
#pragma unroll
            for (int k = 0; k < 2; k++) {
                uint4 v = lds128(sb + SM_SP + tid * 32 + k * 16);
                uint32_t* w = reinterpret_cast<uint32_t*>(&v);
#pragma unroll
                for (int i = 0; i < 4; i++) {
                    const float p0 = ex2((bf_lo(w[i]) - M) * LOG2E), p1 = ex2((bf_hi(w[i]) - M) * LOG2E);
                    l += p0 + p1;
                    w[i] = pack_bf(p0, p1);
                }
                sts128(sb + SM_SP + tid * 32 + k * 16, v);
            }
            l += __shfl_xor_sync(0xffffffffu, l, 1); l += __shfl_xor_sync(0xffffffffu, l, 2);
            l += __shfl_xor_sync(0xffffffffu, l, 8); l += __shfl_xor_sync(0xffffffffu, l, 16);
            if (lane == 0 || lane == 4) sts32(sb + SM_ST + 64 + (h * 8 + warp) * 4, __float_as_uint(l));
            async8();
            if (tid == 0 || tid == 4) {
                const uint4 l0 = lds128(sb + SM_ST + 64 + h * 32), l1 = lds128(sb + SM_ST + 64 + h * 32 + 16);
                const float L = ((__uint_as_float(l0.x) + __uint_as_float(l0.y)) + (__uint_as_float(l0.z) + __uint_as_float(l0.w))) +
                                ((__uint_as_float(l1.x) + __uint_as_float(l1.y)) + (__uint_as_float(l1.z) + __uint_as_float(l1.w)));
                st_pkt2(&gs->ml[cta][h * 2], __float_as_uint(M), __float_as_uint(L), tag);
            }
            __syncwarp();
        }
        mod2_phase();
        TS(7);
        float oacc0[4] = {0.f, 0.f, 0.f, 0.f}, oacc1[4] = {0.f, 0.f, 0.f, 0.f};
        float f0 = 0.f, f1 = 0.f;
        const uint32_t voff = (warp >> 2) * 8192 + rowl * 128 + (((2 * (warp & 3) + (mi & 1)) ^ kap) << 4);
        const u64* odst = &gs->o[cta][c & 1][warp][g][0];
#pragma unroll 1
        for (int t = 0; t < NTILES; t++) {
            const int s = t & 7;
            uint4 pb[2];
            pb[0] = lds128(spw + t * 256); pb[1] = lds128(spw + t * 256 + 16);
            mbar_wait(BAR(B_KVFULL + s), (t >> 3) & 1);
            if ((t & 3) == 3) TS(32 + (t >> 2));
            const uint32_t va = sb + SM_RING + s * TILE_BYTES + voff;
#pragma unroll
            for (int i = 0; i < 2; i++) {
                uint32_t u[4], v[4];
                ldsm4t(u, va + (2 * i) * 2048);
                ldsm4t(v, va + (2 * i + 1) * 2048);
                mma16816(oacc0, u[0], u[1], u[2], u[3], pb[i].x, pb[i].y);
                mma16816(oacc1, v[0], v[1], v[2], v[3], pb[i].z, pb[i].w);
            }
            __syncwarp();
            if (lane == 0) mbar_arrive(BAR(B_KVEMPTY + s));
            if (t == TUNE_RST) clear_own();
            if (t == TUNE_PRE) {
                preload_tail();
                mbar_wait(BAR(B_FAC), 0);
                f0 = ldsf(sb + SM_FAC); f1 = ldsf(sb + SM_FAC + 4);
            }
        }
        TS(8);
        {
            const float f = (c & 1) ? f1 : f0;
            const float u = (c & 1) ? oacc0[1] + oacc1[1] : oacc0[0] + oacc1[0], v = (c & 1) ? oacc0[3] + oacc1[3] : oacc0[2] + oacc1[2];
            st_pkt2_if<0>(c < 2, odst, u * f, v * f, tag);
        }
    }
    TS(9);
    const uint32_t vpb = sb + SM_VP + (g & 1) * (VPSTRIDE * 2) + c * 4;
    if (nO > 0) {
        const int j = lane & 7, s = (lane >> 3) & 3, b = warp & 1, u = warp >> 1;
        const uint4* dst = &gs->p2[wj][warp * 32 + c * 8 + g];
        if (u < nO) {
            const int row = o_r0 + 16 * u;
            const int hq = row >> 7;
            const int r = 16 * u + j + 8 * (s & 1);
            const int grp = nO == 3 ? (r * 43) >> 8 : r >> 2, rr = r - grp * 2 * nO;
            const uint32_t vd = sb + SM_VP + b * (VPSTRIDE * 2) + (16 * (rr >> 1) + (rr & 1) * 8 + grp) * 2;
            uint32_t a[1], e[1];
            pollN<1>(&gs->o[b * 64 + (hq >> 1) * 4 + s][hq & 1][(row >> 4) & 7][j][0], 0, tag, a, e);
            float o0 = __uint_as_float(a[0]), o1 = __uint_as_float(e[0]);
            o0 += __shfl_xor_sync(0xffffffffu, o0, 8); o1 += __shfl_xor_sync(0xffffffffu, o1, 8);
            o0 += __shfl_xor_sync(0xffffffffu, o0, 16); o1 += __shfl_xor_sync(0xffffffffu, o1, 16);
            const uint32_t pk = pack_bf(o0, o1);
            if (s < 2) asm volatile("st.shared.b16 [%0], %1;" ::"r"(vd), "h"((unsigned short)(s ? pk >> 16 : pk)) : "memory");
        }
        uint32_t wof[4][3][4];
        {
            const uint32_t ab = sb + SM_X + kap * (2 * nO * ROWB + 16) + (mi >> 1) * ROWB + (mi & 1) * 16 + warp * 128;
#pragma unroll
            for (int i = 0; i < 4; i++) mbar_wait(BAR(B_MID + i), 0);
#pragma unroll
            for (int i = 0; i < 4; i++) {
                ldsm4t(wof[i][0], ab + i * 32);
                ldsm4t(wof[i][1], ab + i * 32 + 2 * ROWB);
                ldsm4t(wof[i][2], ab + i * 32 + 4 * ROWB);
            }
        }
        csync();
        TS(10);
        uint32_t b0[3], b1[3];
#pragma unroll
        for (int k = 0; k < 3; k++) { b0[k] = lds32(vpb + k * 32); b1[k] = lds32(vpb + k * 32 + 16); }
        float acc[4][4];
#pragma unroll
        for (int i = 0; i < 4; i++) { acc[i][0] = acc[i][1] = acc[i][2] = acc[i][3] = 0.f; mma16816(acc[i], wof[i][0][0], wof[i][0][1], wof[i][0][2], wof[i][0][3], b0[0], b1[0]); }
#pragma unroll
        for (int i = 0; i < 4; i++) mma16816(acc[i], wof[i][1][0], wof[i][1][1], wof[i][1][2], wof[i][1][3], b0[1], b1[1]);
        if (nO == 3) {
#pragma unroll
            for (int i = 0; i < 4; i++) mma16816(acc[i], wof[i][2][0], wof[i][2][1], wof[i][2][2], wof[i][2][3], b0[2], b1[2]);
        }
        publish4(acc, c, dst, t2);
        TSL(80 + warp);
    }
    TS(11);
    uint32_t x1v[2] = {0, 0};
    auto sum8 = [&](uint32_t (&r)[2]) {
        float v[4] = {0.f, 0.f, 0.f, 0.f}, w[4] = {0.f, 0.f, 0.f, 0.f};
#pragma unroll
        for (int k = 0; k < 8; k += 2) {
            const uint4 a = lds128(sb + SM_SP + k * 64 + (lane & 3) * 16), e = lds128(sb + SM_SP + k * 64 + 64 + (lane & 3) * 16);
            v[0] += __uint_as_float(a.x); v[1] += __uint_as_float(a.y); v[2] += __uint_as_float(a.z); v[3] += __uint_as_float(a.w);
            w[0] += __uint_as_float(e.x); w[1] += __uint_as_float(e.y); w[2] += __uint_as_float(e.z); w[3] += __uint_as_float(e.w);
        }
        r[0] = pack_bf(v[0] + w[0], v[1] + w[1]); r[1] = pack_bf(v[2] + w[2], v[3] + w[3]);
    };
    if (reducer && warp < 8) {
        gather_sum(&gs->p2[(warp < 6 ? warp : 0) * 16 + (lane >> 2)][cta * 4 + (lane & 3)], warp < 6, t2, sb + SM_SP + warp * 64, lane);
        if (warp == 0) {
            TS(12);
            async8();
            TS(13);
            uint32_t r[2];
            sum8(r);
            x1v[0] = hadd2(xin[0], hmul2(gav[0], r[0])); x1v[1] = hadd2(xin[1], hmul2(gav[1], r[1]));
            if (lane < 16) st_pkt2(&gs->x1[lane >> 2][cta][(lane & 3) * 2], x1v[0], x1v[1], tag);
            __syncwarp();
        } else {
            asm volatile("bar.arrive 2, 256;" ::: "memory");
        }
    }
    TSL(60 + warp);
    {
        const uint32_t pb = ((mi & 1) ? (warp < 8 ? sb + SM_W3 + warp * BOX_BYTES : sb + SM_W3B8)
                                      : (warp < 8 ? sb + SM_W1 + warp * BOX_BYTES : sb + SM_W1B8)) + rowl * 64 + (sw64 << 4);
        const uint32_t pe = sb + SM_XA + (mi & 1) * 18432 + (warp * 64 + rowl) * 32 + (((rowl >> 2) & 1) << 4);
        const uint32_t ab = (kap < 7 ? sb + SM_W2 + kap * (4 * ROWB + 16) : sb + SM_W2G7) + (mi >> 1) * ROWB + (mi & 1) * 16 + warp * 128;
        const uint32_t aeb = sb + SM_XW2E + kap * (2 * ROWB + 16) + (mi >> 1) * ROWB + (mi & 1) * 16 + warp * 128;
        const uint4* dst = &gs->p4[cta][warp * 32 + c * 8 + g];
        const int ar = tid >> 1;
        const uint32_t ared = sb + SM_RED + ((ar >> 3) * 32 + (ar & 7) * 2 + (tid & 1)) * 4;
        const uint32_t avp = sb + SM_VP + (tid & 1) * (VPSTRIDE * 2) +
                             (ar < 32 ? 16 * ((ar & 3) >> 1) + (ar & 1) * 8 + (ar >> 2) : 32 + (ar & 1) * 8 + ((ar - 32) >> 1)) * 2;
        uint32_t af[4][4][4], ae[4][2][4], wf[4][3][4];
        auto load_frags = [&]() {
        if (typeA) {
#pragma unroll
            for (int i = 0; i < 4; i++) mbar_wait(BAR(B_MID + i), 0);
#pragma unroll
            for (int s = 0; s < 4; s++) { ldsm4t(ae[s][0], pe + s * 512); ldsm4t(ae[s][1], (pe ^ 16) + s * 512); ldsm4t(wf[s][2], aeb + s * 32); }
        }
        mbar_wait(BAR(B_F + warp), 0);
#pragma unroll
        for (int s = 0; s < 4; s++)
#pragma unroll
            for (int j = 0; j < 4; j++) ldsm4t(af[s][j], (pb ^ (j << 4)) + s * 1024);
        };
        const uint4 mb = lds128(sb + SM_MB + tid * 16);
        TSL(40 + warp);
        uint32_t a[2], e[2];
        const int xoff = ((tid >> 3) * 2 + ((tid >> 1) & 1)) * 16 + ((tid >> 2) & 1) * 4 + (tid & 1) * 2;
        pollN<2>(&gs->x1[cta & 3][0][0] + xoff, -xoff, tag, a, e);
        if (tid == 256) mbar_arrive(BAR(B_OPEN));
        TSL(50 + warp);
        uint32_t mean2; float r0, r1;
        ln_stats(a[0], e[0], a[1], sb + SM_ST, warp, lane, mean2, r0, r1);
        const uint32_t ha = modulate2(a[0], mean2, r0, r1, mb.x, mb.y);
        const uint32_t hb = modulate2(e[0], mean2, r0, r1, mb.z, mb.w);
        sts32(sb + SM_HB + tid * 4, __byte_perm(ha, hb, 0x5410));
        sts32(sb + SM_HB + HSTRIDE * 2 + tid * 4, __byte_perm(ha, hb, 0x7632));
        __syncwarp();
        load_frags();
        float acc[6][4];
#pragma unroll
        for (int j = 0; j < 6; j++) acc[j][0] = acc[j][1] = acc[j][2] = acc[j][3] = 0.f;
#pragma unroll
        for (int s = 0; s < 4; s++) {
            const uint32_t b0 = lds32(hbo + s * 32), b1 = lds32(hbo + s * 32 + 16);
#pragma unroll
            for (int j = 0; j < 4; j++) mma16816(acc[j], af[s][j][0], af[s][j][1], af[s][j][2], af[s][j][3], b0, b1);
            if (typeA) {
                mma16816(acc[4], ae[s][0][0], ae[s][0][1], ae[s][0][2], ae[s][0][3], b0, b1);
                mma16816(acc[5], ae[s][1][0], ae[s][1][1], ae[s][1][2], ae[s][1][3], b0, b1);
            }
        }
        if (c == 0) {
#pragma unroll
            for (int j = 0; j < 6; j++) { sts64f(redw + j * 128, acc[j][0], acc[j][1]); sts64f(redw + j * 128 + 64, acc[j][2], acc[j][3]); }
        }
        TS(15);
        csync();
        if (tid < (typeA ? 96 : 64)) {
            const uint32_t gu = pack_bf(red9(ared, 0), red9(ared, 16));
            const uint32_t sg = pack_bf(silu_f(bf_lo(gu)), 0.f);
            const uint32_t hh = hmul2(sg, gu >> 16);
            asm volatile("st.shared.b16 [%0], %1;" ::"r"(avp), "h"((unsigned short)hh) : "memory");
        }
#pragma unroll
        for (int i = 0; i < 4; i++) mbar_wait(BAR(B_W2 + i), 0);
#pragma unroll
        for (int i = 0; i < 4; i++) { ldsm4t(wf[i][0], ab + i * 32); ldsm4t(wf[i][1], ab + i * 32 + 2 * ROWB); }
        csync();
        TS(18);
        uint32_t b0[3], b1[3];
#pragma unroll
        for (int k = 0; k < 3; k++) { b0[k] = lds32(vpb + k * 32); b1[k] = lds32(vpb + k * 32 + 16); }
        float o[4][4];
#pragma unroll
        for (int i = 0; i < 4; i++) { o[i][0] = o[i][1] = o[i][2] = o[i][3] = 0.f; mma16816(o[i], wf[i][0][0], wf[i][0][1], wf[i][0][2], wf[i][0][3], b0[0], b1[0]); }
#pragma unroll
        for (int i = 0; i < 4; i++) mma16816(o[i], wf[i][1][0], wf[i][1][1], wf[i][1][2], wf[i][1][3], b0[1], b1[1]);
        if (typeA) {
#pragma unroll
            for (int i = 0; i < 4; i++) mma16816(o[i], wf[i][2][0], wf[i][2][1], wf[i][2][2], wf[i][2][3], b0[2], b1[2]);
        }
        publish4(o, c, dst, t2);
    }
    TS(19);
    if (reducer && warp < 8) {
        gather_sum(&gs->p4[warp * 16 + (lane >> 2)][cta * 4 + (lane & 3)], true, t2, sb + SM_SP + warp * 64, lane);
        if (warp == 0) {
            async8();
            uint32_t r[2];
            sum8(r);
            const uint32_t y0 = hadd2(x1v[0], hmul2(gbv[0], r[0])), y1 = hadd2(x1v[1], hmul2(gbv[1], r[1]));
            uint32_t* o32 = reinterpret_cast<uint32_t*>(out);
            if (lane < 8) o32[(lane >> 2) * (D_ / 2) + (rcol >> 1)] = __byte_perm(y0, y1, (lane & 4) ? 0x7632 : 0x5410);
            if (cta == 0 && lane == 0) asm volatile("st.relaxed.gpu.global.u32 [%0], %1;" ::"l"(&gs->epoch), "r"(tag) : "memory");
            TS(20);
        } else {
            asm volatile("bar.arrive 2, 256;" ::: "memory");
        }
    }
}

typedef CUresult (*EncodeFn)(CUtensorMap*, CUtensorMapDataType, cuuint32_t, void*, const cuuint64_t*, const cuuint64_t*, const cuuint32_t*,
                             const cuuint32_t*, CUtensorMapInterleave, CUtensorMapSwizzle, CUtensorMapL2promotion, CUtensorMapFloatOOBfill);

void make_map(EncodeFn fn, CUtensorMap* m, const void* p, uint64_t cols, uint64_t rows, uint32_t bcols, uint32_t brows,
              CUtensorMapSwizzle sw, CUtensorMapL2promotion pr) {
    cuuint64_t dims[2] = {cols, rows};
    cuuint64_t strides[1] = {cols * 2};
    cuuint32_t box[2] = {bcols, brows};
    cuuint32_t es[2] = {1, 1};
    fn(m, CU_TENSOR_MAP_DATA_TYPE_BFLOAT16, 2, const_cast<void*>(p), dims, strides, box, es, CU_TENSOR_MAP_INTERLEAVE_NONE, sw, pr,
       CU_TENSOR_MAP_FLOAT_OOB_FILL_NONE);
}

}

extern "C" void kernel_launch(void* const* d_in, const int* in_sizes, int n_in, void* d_out, int out_size) {
    (void)in_sizes; (void)n_in; (void)out_size;
    static EncodeFn enc = nullptr;
    if (!enc) {
        void* fp = nullptr;
        cudaDriverEntryPointQueryResult qr;
        cudaGetDriverEntryPoint("cuTensorMapEncodeTiled", &fp, cudaEnableDefault, &qr);
        enc = (EncodeFn)fp;
        cudaFuncSetAttribute(fused_block_kernel, cudaFuncAttributeMaxDynamicSharedMemorySize, SM_TOTAL);
    }
    const __nv_bfloat16* x    = (const __nv_bfloat16*)d_in[0];
    const __nv_bfloat16* wo   = (const __nv_bfloat16*)d_in[4];
    const __nv_bfloat16* w2   = (const __nv_bfloat16*)d_in[8];
    const __nv_bfloat16* cvec = (const __nv_bfloat16*)d_in[9];
    CUtensorMap tk, tv, tq, tm, t1, t3, t1x, t3x;
    make_map(enc, &tk, d_in[1], DH, 2ull * HKV * SK, 64, TILE_KEYS, CU_TENSOR_MAP_SWIZZLE_128B, CU_TENSOR_MAP_L2_PROMOTION_L2_256B);
    make_map(enc, &tv, d_in[2], DH, 2ull * HKV * SK, 64, TILE_KEYS, CU_TENSOR_MAP_SWIZZLE_128B, CU_TENSOR_MAP_L2_PROMOTION_L2_256B);
    make_map(enc, &tq, d_in[3], NQ, D_, 32, 64, CU_TENSOR_MAP_SWIZZLE_64B, CU_TENSOR_MAP_L2_PROMOTION_L2_128B);
    make_map(enc, &tm, d_in[10], NMOD, D_, 32, 64, CU_TENSOR_MAP_SWIZZLE_64B, CU_TENSOR_MAP_L2_PROMOTION_L2_128B);
    make_map(enc, &t1, d_in[6], FF, D_, 32, 64, CU_TENSOR_MAP_SWIZZLE_64B, CU_TENSOR_MAP_L2_PROMOTION_L2_128B);
    make_map(enc, &t3, d_in[7], FF, D_, 32, 64, CU_TENSOR_MAP_SWIZZLE_64B, CU_TENSOR_MAP_L2_PROMOTION_L2_128B);
    make_map(enc, &t1x, d_in[6], FF, D_, 16, 192, CU_TENSOR_MAP_SWIZZLE_32B, CU_TENSOR_MAP_L2_PROMOTION_L2_128B);
    make_map(enc, &t3x, d_in[7], FF, D_, 16, 192, CU_TENSOR_MAP_SWIZZLE_32B, CU_TENSOR_MAP_L2_PROMOTION_L2_128B);
    fused_block_kernel<<<NCTA, NTHREADS, SM_TOTAL>>>(tk, tv, tq, tm, t1, t3, t1x, t3x, x, wo, w2, cvec, (const __nv_bfloat16*)d_in[10], (__nv_bfloat16*)d_out);
}
```
